```python
import torch

def _softmax(x, axis=-1):
    return torch.softmax(x, dim=axis)
def _gelu(x):
    return torch.nn.functional.gelu(x, approximate="tanh")
def _silu(x):
    return torch.nn.functional.silu(x)
def _sigmoid(x):
    return torch.sigmoid(x)
def _layernorm(x, axis=-1, eps=1e-5):
    m = x.mean(dim=axis, keepdim=True)
    v = x.var(dim=axis, keepdim=True, unbiased=False)
    return (x - m) / torch.sqrt(v + eps)
def _scatter_add(tgt, idx, src, axis=0):
    return tgt.clone().index_add_(axis, idx, src)
def _segment_sum(src, seg, n):
    out = torch.zeros((n,) + src.shape[1:], dtype=src.dtype)
    return out.index_add_(0, seg, src)
def _pad(x, pw):
    flat = tuple(v for pair in reversed(pw) for v in pair)
    return torch.nn.functional.pad(x, flat)

kernel_name = 'standalone__gqa_block_cached__near_ridge'

def setup_inputs():

    _w = (lambda a: (lambda t: t.to(torch.bfloat16) if t.is_floating_point() else t)(torch.as_tensor(a)))
    B, Sq, D = 8, 96, 576
    Hq, Hkv, Sk, Dh = 32, 16, 1024, 128
    assert Hq % Hkv == 0, (Hq, Hkv)
    return {
        "x": _w((lambda *s: torch.randn(*s, dtype=torch.bfloat16) * 0.8)(B, Sq, D)),
        "k_cache": _w((lambda *s: torch.randn(*s, dtype=torch.bfloat16) * 0.8)(B, Hkv, Sk, Dh)),
        "v_cache": _w((lambda *s: torch.randn(*s, dtype=torch.bfloat16) * 0.05)(B, Hkv, Sk, Dh)),
        "wq": _w((lambda *s: torch.randn(*s, dtype=torch.bfloat16) * 0.8)(D, Hq * Dh) * (D ** -0.5)),
        "wo": _w((lambda *s: torch.randn(*s, dtype=torch.bfloat16) * 0.05)(Hq * Dh, D) * ((Hq * Dh) ** -0.5)),
    }

def reference(x, k_cache, v_cache, wq, wo):
    B, Sq, D = x.shape
    Hq, Dh = 32, 128
    Hkv = k_cache.shape[1]
    rep = Hq // Hkv
    q = (lambda x, *d: x.permute(*d))((x @ wq).reshape(B, Sq, Hq, Dh), 0, 2, 1, 3)
    k = (lambda x, n, axis: torch.repeat_interleave(x, n, dim=axis))(k_cache, rep, axis=1)
    v = (lambda x, n, axis: torch.repeat_interleave(x, n, dim=axis))(v_cache, rep, axis=1)
    scores = torch.einsum("bhqd,bhkd->bhqk", q, k) * (Dh ** -0.5)
    p = _softmax(scores, axis=-1)
    o = torch.einsum("bhqk,bhkd->bhqd", p, v)
    return (lambda x, *d: x.permute(*d))(o, 0, 2, 1, 3).reshape(B, Sq, Hq * Dh) @ wo
```

```cpp
#include <cuda_runtime.h>
#include <cuda_bf16.h>
#include <cuda.h>
#include <stdint.h>

#define INFLIGHT0 2
#define INFLIGHT 3
#define PF_W 2
#define PF_UNITS 14
#define PF_T0 2500
#define PF_PACE 1080
#define PF_LAG 2000
#define WO_DELAY 2

namespace {

constexpr int NB = 8, SQ = 96, DM = 576, HKV = 16, SK = 1024, DH = 128;
constexpr int NTHREADS = 512;

constexpr uint32_t Q_OFF    = 0;
constexpr uint32_t Q_HALF   = 192 * 128;
constexpr uint32_t RING_OFF = 2 * Q_HALF;
constexpr uint32_t P1_STAGE = 22528;
constexpr uint32_t P1_XOFF  = 16384;
constexpr int      P1_CH    = 18;
constexpr uint32_t SLOT     = 16384;
constexpr int      NSLOT    = 11;
constexpr uint32_t BAR_OFF  = RING_OFF + NSLOT * SLOT;
__host__ __device__ constexpr uint32_t p1_stage_off(int st) { return st < 2 ? Q_OFF + st * P1_STAGE : BAR_OFF - (4 - st) * P1_STAGE; }
constexpr uint32_t SMEM_BYTES = BAR_OFF + 512 + 1024;
constexpr uint32_t B_P1FULL = 0, B_P1EMPTY = 4, B_FULL = 8, B_EMPTY = 19, B_WOFULL = 30, B_TRIG = 39, B_STAGED = 42, B_P1TAIL = 51;

#define KV_PROMO CU_TENSOR_MAP_L2_PROMOTION_L2_128B
#define ZERO_AT 20
#define KV_START 1
#define PF_WO_AT 32
#define SPIN_LIMIT (1 << 22)

__device__ unsigned g_epoch[NB * HKV];
__device__ unsigned g_cnt[NB * 32];
#define TS(i) do {} while (0)
#define TR(n, i) do {} while (0)

template <int TA, int TB>
__device__ __forceinline__ void wgmma_ss_n96(float (&d)[48], uint64_t da, uint64_t db, int scale_d) {
    asm volatile("{\n.reg .pred p;\nsetp.ne.b32 p, %50, 0;\n"
        "wgmma.mma_async.sync.aligned.m64n96k16.f32.bf16.bf16 {%0, %1, %2, %3, %4, %5, %6, %7, %8, %9, %10, %11, %12, %13, %14, %15, %16, %17, %18, %19, %20, %21, %22, %23, %24, %25, %26, %27, %28, %29, %30, %31, %32, %33, %34, %35, %36, %37, %38, %39, %40, %41, %42, %43, %44, %45, %46, %47}, %48, %49, p, 1, 1, %51, %52;\n}\n"
        : "+f"(d[0]), "+f"(d[1]), "+f"(d[2]), "+f"(d[3]), "+f"(d[4]), "+f"(d[5]), "+f"(d[6]), "+f"(d[7]), "+f"(d[8]), "+f"(d[9]), "+f"(d[10]), "+f"(d[11]), "+f"(d[12]), "+f"(d[13]), "+f"(d[14]), "+f"(d[15]), "+f"(d[16]), "+f"(d[17]), "+f"(d[18]), "+f"(d[19]), "+f"(d[20]), "+f"(d[21]), "+f"(d[22]), "+f"(d[23]), "+f"(d[24]), "+f"(d[25]), "+f"(d[26]), "+f"(d[27]), "+f"(d[28]), "+f"(d[29]), "+f"(d[30]), "+f"(d[31]), "+f"(d[32]), "+f"(d[33]), "+f"(d[34]), "+f"(d[35]), "+f"(d[36]), "+f"(d[37]), "+f"(d[38]), "+f"(d[39]), "+f"(d[40]), "+f"(d[41]), "+f"(d[42]), "+f"(d[43]), "+f"(d[44]), "+f"(d[45]), "+f"(d[46]), "+f"(d[47])
        : "l"(da), "l"(db), "r"(scale_d), "n"(TA), "n"(TB));
}
template <int TA, int TB>
__device__ __forceinline__ void wgmma_ss_n64(float (&d)[32], uint64_t da, uint64_t db, int scale_d) {
    asm volatile("{\n.reg .pred p;\nsetp.ne.b32 p, %34, 0;\n"
        "wgmma.mma_async.sync.aligned.m64n64k16.f32.bf16.bf16 {%0, %1, %2, %3, %4, %5, %6, %7, %8, %9, %10, %11, %12, %13, %14, %15, %16, %17, %18, %19, %20, %21, %22, %23, %24, %25, %26, %27, %28, %29, %30, %31}, %32, %33, p, 1, 1, %35, %36;\n}\n"
        : "+f"(d[0]), "+f"(d[1]), "+f"(d[2]), "+f"(d[3]), "+f"(d[4]), "+f"(d[5]), "+f"(d[6]), "+f"(d[7]), "+f"(d[8]), "+f"(d[9]), "+f"(d[10]), "+f"(d[11]), "+f"(d[12]), "+f"(d[13]), "+f"(d[14]), "+f"(d[15]), "+f"(d[16]), "+f"(d[17]), "+f"(d[18]), "+f"(d[19]), "+f"(d[20]), "+f"(d[21]), "+f"(d[22]), "+f"(d[23]), "+f"(d[24]), "+f"(d[25]), "+f"(d[26]), "+f"(d[27]), "+f"(d[28]), "+f"(d[29]), "+f"(d[30]), "+f"(d[31])
        : "l"(da), "l"(db), "r"(scale_d), "n"(TA), "n"(TB));
}
template <int TB>
__device__ __forceinline__ void wgmma_rs_n128(float (&d)[64], uint32_t a0, uint32_t a1, uint32_t a2, uint32_t a3, uint64_t db, int scale_d) {
    asm volatile("{\n.reg .pred p;\nsetp.ne.b32 p, %69, 0;\n"
        "wgmma.mma_async.sync.aligned.m64n128k16.f32.bf16.bf16 {%0, %1, %2, %3, %4, %5, %6, %7, %8, %9, %10, %11, %12, %13, %14, %15, %16, %17, %18, %19, %20, %21, %22, %23, %24, %25, %26, %27, %28, %29, %30, %31, %32, %33, %34, %35, %36, %37, %38, %39, %40, %41, %42, %43, %44, %45, %46, %47, %48, %49, %50, %51, %52, %53, %54, %55, %56, %57, %58, %59, %60, %61, %62, %63}, {%64, %65, %66, %67}, %68, p, 1, 1, %70;\n}\n"
        : "+f"(d[0]), "+f"(d[1]), "+f"(d[2]), "+f"(d[3]), "+f"(d[4]), "+f"(d[5]), "+f"(d[6]), "+f"(d[7]), "+f"(d[8]), "+f"(d[9]), "+f"(d[10]), "+f"(d[11]), "+f"(d[12]), "+f"(d[13]), "+f"(d[14]), "+f"(d[15]), "+f"(d[16]), "+f"(d[17]), "+f"(d[18]), "+f"(d[19]), "+f"(d[20]), "+f"(d[21]), "+f"(d[22]), "+f"(d[23]), "+f"(d[24]), "+f"(d[25]), "+f"(d[26]), "+f"(d[27]), "+f"(d[28]), "+f"(d[29]), "+f"(d[30]), "+f"(d[31]), "+f"(d[32]), "+f"(d[33]), "+f"(d[34]), "+f"(d[35]), "+f"(d[36]), "+f"(d[37]), "+f"(d[38]), "+f"(d[39]), "+f"(d[40]), "+f"(d[41]), "+f"(d[42]), "+f"(d[43]), "+f"(d[44]), "+f"(d[45]), "+f"(d[46]), "+f"(d[47]), "+f"(d[48]), "+f"(d[49]), "+f"(d[50]), "+f"(d[51]), "+f"(d[52]), "+f"(d[53]), "+f"(d[54]), "+f"(d[55]), "+f"(d[56]), "+f"(d[57]), "+f"(d[58]), "+f"(d[59]), "+f"(d[60]), "+f"(d[61]), "+f"(d[62]), "+f"(d[63])
        : "r"(a0), "r"(a1), "r"(a2), "r"(a3), "l"(db), "r"(scale_d), "n"(TB));
}

__device__ __forceinline__ void wg_fence()  { asm volatile("wgmma.fence.sync.aligned;" ::: "memory"); }
__device__ __forceinline__ void wg_commit() { asm volatile("wgmma.commit_group.sync.aligned;" ::: "memory"); }
template <int N> __device__ __forceinline__ void wg_wait() { asm volatile("wgmma.wait_group.sync.aligned %0;" :: "n"(N) : "memory"); }
template <int N> __device__ __forceinline__ void reg_fence(float (&d)[N]) {
#pragma unroll
    for (int i = 0; i < N; i++) asm volatile("" : "+f"(d[i]) :: "memory");
}
template <int N> __device__ __forceinline__ void reg_fence_u(uint32_t (&d)[N]) {
#pragma unroll
    for (int i = 0; i < N; i++) asm volatile("" : "+r"(d[i]) :: "memory");
}
#define F(x) __uint_as_float(x)
__device__ __forceinline__ uint64_t desc(uint32_t lo) { return ((uint64_t)((1024u >> 4) | (1u << 30)) << 32) | lo; }
__device__ __forceinline__ uint64_t desc64(uint32_t lo) { return ((uint64_t)((512u >> 4) | (2u << 30)) << 32) | lo; }
__device__ __forceinline__ void mbar_init(uint32_t bar, uint32_t cnt) { asm volatile("mbarrier.init.shared::cta.b64 [%0], %1;" :: "r"(bar), "r"(cnt) : "memory"); }
__device__ __forceinline__ void mbar_expect_tx(uint32_t bar, uint32_t bytes) { asm volatile("mbarrier.arrive.expect_tx.shared::cta.b64 _, [%0], %1;" :: "r"(bar), "r"(bytes) : "memory"); }
__device__ __forceinline__ void mbar_arrive(uint32_t bar) { asm volatile("mbarrier.arrive.shared::cta.b64 _, [%0];" :: "r"(bar) : "memory"); }
__device__ __forceinline__ void mbar_arrive_n(uint32_t bar, uint32_t n) { asm volatile("mbarrier.arrive.shared::cta.b64 _, [%0], %1;" :: "r"(bar), "r"(n) : "memory"); }
__device__ __forceinline__ bool mbar_try(uint32_t bar, uint32_t parity) {
    uint32_t ok;
    asm volatile("{\n.reg .pred p;\nmbarrier.try_wait.parity.shared::cta.b64 p, [%1], %2;\nselp.b32 %0, 1, 0, p;\n}" : "=r"(ok) : "r"(bar), "r"(parity) : "memory");
    return ok;
}
__device__ __forceinline__ void mbar_wait(uint32_t bar, uint32_t parity) {
    asm volatile("{\n.reg .pred p;\n.reg .u32 c;\nmov.u32 c, 0;\n"
                 "WAIT_LOOP:\nmbarrier.try_wait.parity.shared::cta.b64 p, [%0], %1;\n@p bra WAIT_DONE;\n"
                 "add.u32 c, c, 1;\nsetp.lt.u32 p, c, 4194304;\n@p bra WAIT_LOOP;\ntrap;\nWAIT_DONE:\n}" :: "r"(bar), "r"(parity) : "memory");
}
__device__ __forceinline__ void tma2d(uint32_t dst, const CUtensorMap* m, int c0, int c1, uint32_t bar) {
    asm volatile("cp.async.bulk.tensor.2d.shared::cluster.global.mbarrier::complete_tx::bytes [%0], [%1, {%3, %4}], [%2];"
                 :: "r"(dst), "l"(m), "r"(bar), "r"(c0), "r"(c1) : "memory");
}
__device__ __forceinline__ void tma3d(uint32_t dst, const CUtensorMap* m, int c0, int c1, int c2, uint32_t bar) {
    asm volatile("cp.async.bulk.tensor.3d.shared::cluster.global.mbarrier::complete_tx::bytes [%0], [%1, {%3, %4, %5}], [%2];"
                 :: "r"(dst), "l"(m), "r"(bar), "r"(c0), "r"(c1), "r"(c2) : "memory");
}
__device__ __forceinline__ void tma3d_hint(uint32_t dst, const CUtensorMap* m, int c0, int c1, int c2, uint32_t bar, uint64_t pol) {
    asm volatile("cp.async.bulk.tensor.3d.shared::cluster.global.mbarrier::complete_tx::bytes.L2::cache_hint [%0], [%1, {%3, %4, %5}], [%2], %6;"
                 :: "r"(dst), "l"(m), "r"(bar), "r"(c0), "r"(c1), "r"(c2), "l"(pol) : "memory");
}
__device__ __forceinline__ void tma2d_pf(const CUtensorMap* m, int c0, int c1) {
    asm volatile("cp.async.bulk.prefetch.tensor.2d.L2.global [%0, {%1, %2}];" :: "l"(m), "r"(c0), "r"(c1) : "memory");
}
__device__ __forceinline__ void tma3d_pf(const CUtensorMap* m, int c0, int c1, int c2) {
    asm volatile("cp.async.bulk.prefetch.tensor.3d.L2.global [%0, {%1, %2, %3}];" :: "l"(m), "r"(c0), "r"(c1), "r"(c2) : "memory");
}
__device__ __forceinline__ void prefetch_l2(const void* p) { asm volatile("prefetch.global.L2 [%0];" :: "l"(p)); }
__device__ __forceinline__ void fence_async_smem() { asm volatile("fence.proxy.async.shared::cta;" ::: "memory"); }
__device__ __forceinline__ void bar_consumers() { asm volatile("bar.sync 1, 384;" ::: "memory"); }
__device__ __forceinline__ void tok_wait(int me) { asm volatile("bar.sync %0, 256;" :: "r"(me + 2) : "memory"); }
__device__ __forceinline__ void tok_pass(int to) { asm volatile("bar.arrive %0, 256;" :: "r"(to + 2) : "memory"); }
__device__ __forceinline__ uint32_t pack_bf16(float lo, float hi) {
    uint32_t r; asm("cvt.rn.bf16x2.f32 %0, %1, %2;" : "=r"(r) : "f"(hi), "f"(lo)); return r;
}
__device__ __forceinline__ void stsm_x4(uint32_t addr, uint32_t a, uint32_t b, uint32_t c, uint32_t d) {
    asm volatile("stmatrix.sync.aligned.m8n8.x4.shared.b16 [%0], {%1, %2, %3, %4};" :: "r"(addr), "r"(a), "r"(b), "r"(c), "r"(d) : "memory");
}
__device__ __forceinline__ void stsm_x4_t(uint32_t addr, uint32_t a, uint32_t b, uint32_t c, uint32_t d) {
    asm volatile("stmatrix.sync.aligned.m8n8.x4.trans.shared.b16 [%0], {%1, %2, %3, %4};" :: "r"(addr), "r"(a), "r"(b), "r"(c), "r"(d) : "memory");
}
__device__ __forceinline__ float ex2(float x) { float r; asm("ex2.approx.ftz.f32 %0, %1;" : "=f"(r) : "f"(x)); return r; }
__device__ __forceinline__ bool elect_one() {
    uint32_t p; asm volatile("{\n.reg .pred p;\nelect.sync _|p, 0xffffffff;\nselp.b32 %0, 1, 0, p;\n}" : "=r"(p)); return p;
}

__device__ __forceinline__ void store_T(const float (&acc)[48], uint32_t base, int warp, int lane) {
    const int mi = lane >> 3, r = lane & 7;
    base += ((mi >> 1) * 8 + r) * 128 + (((2 * warp + (mi & 1)) ^ r) << 4);
#pragma unroll
    for (int j = 0; j < 12; j += 2)
        stsm_x4_t(base + j * 1024, pack_bf16(acc[4 * j], acc[4 * j + 1]), pack_bf16(acc[4 * j + 2], acc[4 * j + 3]),
                  pack_bf16(acc[4 * j + 4], acc[4 * j + 5]), pack_bf16(acc[4 * j + 6], acc[4 * j + 7]));
}
__device__ __forceinline__ void store_qT(const float (&acc)[48], uint32_t sb, int tile, int warp, int lane) {
    store_T(acc, sb + Q_OFF + (tile & 1) * Q_HALF + (tile >> 1) * 12288, warp, lane);
}

template <int NT>
__device__ __forceinline__ void phase1(uint32_t sb, uint32_t bars, int t0, int t1, int warp, int lane, long long t_start) {
    float acc0[48], acc1[48];
#pragma unroll 1
    for (int c = 0; c < P1_CH; c++) {
        const int st = c & 3;
        mbar_wait(bars + (B_P1FULL + st) * 8, (c >> 2) & 1);
        if (NT == 2 && threadIdx.x == 0 && !(c & 1)) TS(26 + (c >> 1));
        const uint32_t ws = (sb + p1_stage_off(st)) >> 4, xs = ws + (P1_XOFF >> 4);
        wg_fence();
#pragma unroll
        for (int kk = 0; kk < 2; kk++) {
            const uint64_t db = desc64(xs + kk * 2);
            wgmma_ss_n96<1, 0>(acc0, desc(ws + t0 * 256 + kk * 128), db, (c | kk) != 0);
            if (NT == 2) wgmma_ss_n96<1, 0>(acc1, desc(ws + t1 * 256 + kk * 128), db, (c | kk) != 0);
        }
        wg_commit();
        wg_wait<1>();
        if (c > 0 && lane == 0) mbar_arrive(bars + (c == 16 ? B_P1TAIL : B_P1EMPTY + ((c - 1) & 3)) * 8);
    }
    wg_wait<0>();
    reg_fence(acc0);
    if (NT == 2) reg_fence(acc1);
    if (lane == 0) mbar_arrive(bars + (B_P1EMPTY + 1) * 8);
    mbar_wait(bars + (B_P1EMPTY + 0) * 8, 0);
    mbar_wait(bars + (B_P1EMPTY + 1) * 8, 0);
    store_qT(acc0, sb, t0, warp, lane);
    if (NT == 2) store_qT(acc1, sb, t1, warp, lane);
}

__global__ void __launch_bounds__(NTHREADS, 1)
gqa_fused_kernel(const __grid_constant__ CUtensorMap map_x, const __grid_constant__ CUtensorMap map_wq,
                 const __grid_constant__ CUtensorMap map_k, const __grid_constant__ CUtensorMap map_v,
                 const __grid_constant__ CUtensorMap map_wo, const __grid_constant__ CUtensorMap map_out,
                 const char* __restrict__ gx, const char* __restrict__ gwq, const char* __restrict__ gk,
                 const char* __restrict__ gv, const char* __restrict__ gwo, __nv_bfloat16* __restrict__ out) {
    extern __shared__ __align__(1024) unsigned char smem_raw[];
    long long t_start = 0;
    const uint32_t clk0 = clock();
    uint32_t sb;
    asm volatile("mov.u32 %0, %1;" : "=r"(sb) : "r"(((uint32_t)__cvta_generic_to_shared(smem_raw) + 1023) & ~1023u));
    const uint32_t bars = sb + BAR_OFF;
    const int tid = threadIdx.x, lane = tid & 31;
    const int wg = __shfl_sync(0xffffffff, tid >> 7, 0);
    const int warp = __shfl_sync(0xffffffff, (tid >> 5) & 3, 0);
    const int b = blockIdx.x & 7, h = blockIdx.x >> 3;

    auto load_p1 = [&](int c) {
        const uint32_t fb = bars + (B_P1FULL + (c & 3)) * 8, dst = sb + p1_stage_off(c & 3);
        mbar_expect_tx(fb, P1_STAGE);
        tma3d(dst, &map_wq, 0, c * 32, h * 4, fb);
        tma2d(dst + P1_XOFF, &map_x, c * 32, b * 96, fb);
    };
    if (tid == 384) {
        asm volatile("prefetch.tensormap [%0];" :: "l"(&map_wq) : "memory");
        asm volatile("prefetch.tensormap [%0];" :: "l"(&map_x) : "memory");
#pragma unroll
        for (int i = 0; i < 4; i++) mbar_init(bars + (B_P1FULL + i) * 8, 1);
        fence_async_smem();
#pragma unroll
        for (int c = 0; c < 4; c++) load_p1(c);
        tma3d_pf(&map_wq, 0, (4 + b) * 32, h * 4);
        if (h < 14) tma2d_pf(&map_x, (4 + h) * 32, b * 96);
        if (b < 6) tma3d_pf(&map_wq, 0, (12 + b) * 32, h * 4);
    } else if (tid == 416) {
        asm volatile("prefetch.tensormap [%0];" :: "l"(&map_k) : "memory");
        asm volatile("prefetch.tensormap [%0];" :: "l"(&map_v) : "memory");
#pragma unroll
        for (int i = 0; i < NSLOT; i++) { mbar_init(bars + (B_FULL + i) * 8, 1); mbar_init(bars + (B_EMPTY + i) * 8, 12); }
        fence_async_smem();
    } else if (tid == 0) {
#pragma unroll
        for (int i = 0; i < 4; i++) mbar_init(bars + (B_P1EMPTY + i) * 8, 12);
#pragma unroll
        for (int i = 0; i < 9; i++) { mbar_init(bars + (B_WOFULL + i) * 8, 2); mbar_init(bars + (B_STAGED + i) * 8, 4); }
#pragma unroll
        for (int i = 0; i < 3; i++) mbar_init(bars + (B_TRIG + i) * 8, 1);
        mbar_init(bars + B_P1TAIL * 8, 12);
        fence_async_smem();
    }
    __syncthreads();

    if (wg == 3) {
        asm volatile("setmaxnreg.dec.sync.aligned.u32 80;");
        if (warp == 0) {
#pragma unroll 1
            for (int c = 4; c < P1_CH; c++) {
                mbar_wait(bars + (B_P1EMPTY + (c & 3)) * 8, ((c >> 2) - 1) & 1);
                if (elect_one()) load_p1(c);
                __syncwarp();
            }
            if (lane == 0) {
                TS(50);
                asm volatile("prefetch.tensormap [%0];" :: "l"(&map_out) : "memory");
                mbar_wait(bars + (B_TRIG + 2) * 8, 0);
                asm volatile("fence.proxy.async.global;" ::: "memory");
#pragma unroll 1
                for (int j = 0; j < 9; j++) {
                    mbar_wait(bars + (B_STAGED + j) * 8, 0);
                    asm volatile("cp.reduce.async.bulk.tensor.2d.global.shared::cta.add.tile.bulk_group [%0, {%2, %3}], [%1];"
                                 :: "l"(&map_out), "r"(sb + RING_OFF + ((32 + 2 * j) % NSLOT) * SLOT), "r"(j * 64), "r"(b * SQ) : "memory");
                    asm volatile("cp.async.bulk.commit_group;" ::: "memory");
                    TS(2 + j);
                    if (j >= 1 && j <= 4) {
                        asm volatile("cp.async.bulk.wait_group.read 1;" ::: "memory");
                        mbar_arrive_n(bars + (B_EMPTY + (30 + 2 * j) % NSLOT) * 8, 12);
                    }
                }
                asm volatile("cp.async.bulk.wait_group.read 0;" ::: "memory");
                TS(59);
            }
        } else if (warp == 1) {
            const int kvrow = (b * HKV + h) * SK;
            uint64_t pol;
            asm volatile("createpolicy.fractional.L2::evict_first.b64 %0, 1.0;" : "=l"(pol));
            if (KV_START >= 1) mbar_wait(bars + (B_P1FULL + KV_START - 1) * 8, 0);
            if (elect_one()) {
                const uint32_t ring = sb + RING_OFF;
                auto kv_load = [&](const CUtensorMap* m, int row, uint32_t slot) {
                    const uint32_t fb = bars + B_FULL * 8 + slot * 8;
                    mbar_expect_tx(fb, SLOT);
                    tma3d_hint(ring + slot * SLOT, m, 0, row, 0, fb, pol);
                };
                TS(44);
#pragma unroll
                for (int u = 0; u < NSLOT; u++) {
                    if (u == 8) mbar_wait(bars + B_P1TAIL * 8, 0);
                    if (u < 8) while ((uint32_t)(clock() - clk0) < PF_T0 + (u + 1) * PF_PACE + PF_LAG) {}
                    if (u >= (u < 8 ? INFLIGHT0 : INFLIGHT)) mbar_wait(bars + (B_FULL + u - (u < 8 ? INFLIGHT0 : INFLIGHT)) * 8, 0);
                    const bool isv = u != 0 && !(u & 1);
                    kv_load(isv ? &map_v : &map_k, kvrow + (isv ? (u >> 1) - 1 : (u + 1) >> 1) * 64, u);
                    if (u == 4) TS(36); if (u == 8) TS(37);
                }
                uint32_t slot = 0, ph = 0;
                uint32_t fslot = NSLOT - INFLIGHT, fph = 0;
                auto acquire = [&]() {
                    mbar_wait(bars + B_EMPTY * 8 + slot * 8, ph);
                };
                auto throttle = [&]() {
                    mbar_wait(bars + B_FULL * 8 + fslot * 8, fph);
                    if (++fslot == NSLOT) { fslot = 0; fph ^= 1; }
                };
                auto advance = [&]() { if (++slot == NSLOT) { slot = 0; ph ^= 1; } };
                int row = kvrow + 5 * 64;
#pragma unroll 1
                for (int i = 5; i < 15; i++) {
                    acquire(); throttle(); kv_load(&map_k, row + 64, slot); advance();
                    acquire(); throttle(); kv_load(&map_v, row, slot); advance();
                    row += 64;
                    if (i == ZERO_AT / 2) mbar_arrive(bars + (B_TRIG + 0) * 8);
                    if (i & 1) TS(35 + ((i + 1) >> 1));
                }
                acquire(); throttle(); kv_load(&map_v, row, slot); advance();
                TS(43);
#pragma unroll
                for (int i = 0; i < WO_DELAY; i++) throttle();
                mbar_arrive(bars + (B_TRIG + 1) * 8);
#pragma unroll 1
                for (int j = 0; j < 9; j++) {
                    const uint32_t fb = bars + B_WOFULL * 8 + j * 8;
                    acquire(); mbar_expect_tx(fb, SLOT); tma2d(ring + slot * SLOT, &map_wo, j * 64, h * 256, fb); advance();
                    acquire(); mbar_expect_tx(fb, SLOT); tma2d(ring + slot * SLOT, &map_wo, j * 64, h * 256 + 128, fb); advance();
                }
            }
            if (lane == 0) TS(51);
        } else {
            const int t = tid - 448;
            const uint32_t epoch = g_epoch[blockIdx.x] + 1;
            if (t == 0) asm volatile("prefetch.tensormap [%0];" :: "l"(&map_wo) : "memory");
            if (warp == 3) {
                const char* kb = gk + (size_t)(b * HKV + h) * SK * 256 + lane * 128;
                const char* vb = gv + (size_t)(b * HKV + h) * SK * 256 + lane * 128;
#pragma unroll 1
                for (int i = 0; i < PF_UNITS * 4; i++) {
                    const int u = i >> 2;
                    const bool isv = (u == 31) || (u != 0 && !(u & 1));
                    const int idx = u == 31 ? 15 : (isv ? (u >> 1) - 1 : (u + 1) >> 1);
                    while ((uint32_t)(clock() - clk0) < PF_T0 + i * (PF_PACE / 4)) {}
                    prefetch_l2((isv ? vb : kb) + idx * 16384 + (i & 3) * 4096);
                }
            }
            mbar_wait(bars + (B_TRIG + 0) * 8, 0);
            uint4* o4 = reinterpret_cast<uint4*>(out + (size_t)(b * SQ + 6 * h) * DM);
            for (int i = t; i < 432; i += 64) o4[i] = make_uint4(0, 0, 0, 0);
            __threadfence();
            asm volatile("bar.sync 8, 64;" ::: "memory");
            if (t == 32) {
                atomicAdd(&g_cnt[b * 32], 1);
                unsigned cur; int it = 0;
                do { asm volatile("ld.acquire.gpu.global.u32 %0, [%1];" : "=r"(cur) : "l"(&g_cnt[b * 32]) : "memory"); __nanosleep(100); }
                while ((int)(cur - epoch * 16) < 0 && ++it < SPIN_LIMIT);
                mbar_arrive(bars + (B_TRIG + 2) * 8);
                g_epoch[blockIdx.x] = epoch;
            }
            if (warp == 2) {
                mbar_wait(bars + (B_TRIG + 1) * 8, 0);
#pragma unroll
                for (int j = 2; j < 9; j++) prefetch_l2(gwo + (size_t)(h * 256 + b * 32 + lane) * 1152 + j * 128);
            }
        }
    } else {
        asm volatile("setmaxnreg.inc.sync.aligned.u32 144;");
        if (wg == 0) phase1<2>(sb, bars, 0, 3, warp, lane, t_start);
        else         phase1<1>(sb, bars, wg, 0, warp, lane, t_start);
        fence_async_smem();
        if (tid == 0) TS(0);
        bar_consumers();
        if (tid == 0) TS(1);

        const float scale = 0.08838834764831845f * 1.4426950408889634f;
        float o[64], s[32];
        uint32_t p[16];
        float m0, m1, l0, l1;
        const uint32_t qa = sb + Q_OFF + wg * 8192;
        const uint32_t q_lo = qa >> 4, ring_lo = (sb + RING_OFF) >> 4;
        const int nxt = wg == 2 ? 0 : wg + 1;
        const bool t128_0 = (tid & 127) == 0; (void)t128_0;
        int slot = 0, ph = 0;
        auto issue_qk = [&](int sl) {
            const uint32_t k_lo = ring_lo + sl * (SLOT >> 4);
#pragma unroll
            for (int kk = 0; kk < 8; kk++)
                wgmma_ss_n64<0, 0>(s, desc(q_lo + (kk >> 2) * (Q_HALF >> 4) + (kk & 3) * 2), desc(k_lo + (kk >> 2) * 512 + (kk & 3) * 2), kk != 0);
            wg_commit();
        };
        auto issue_pv = [&](int sl, int accum) {
            const uint32_t v_lo = (ring_lo + sl * (SLOT >> 4)) | ((8192u >> 4) << 16);
#pragma unroll
            for (int kk = 0; kk < 4; kk++)
                wgmma_rs_n128<1>(o, p[4 * kk], p[4 * kk + 1], p[4 * kk + 2], p[4 * kk + 3], desc(v_lo + kk * 128), kk == 0 ? accum : 1);
            wg_commit();
        };
        auto row_max = [&](float& mx0, float& mx1) {
            float a0 = fmaxf(s[0], s[1]), a1 = fmaxf(s[2], s[3]), b0 = fmaxf(s[4], s[5]), b1 = fmaxf(s[6], s[7]);
#pragma unroll
            for (int j = 2; j < 8; j += 2) {
                a0 = fmaxf(a0, fmaxf(s[4 * j], s[4 * j + 1]));     a1 = fmaxf(a1, fmaxf(s[4 * j + 2], s[4 * j + 3]));
                b0 = fmaxf(b0, fmaxf(s[4 * j + 4], s[4 * j + 5])); b1 = fmaxf(b1, fmaxf(s[4 * j + 6], s[4 * j + 7]));
            }
            mx0 = fmaxf(a0, b0); mx1 = fmaxf(a1, b1);
            mx0 = fmaxf(mx0, __shfl_xor_sync(0xffffffff, mx0, 1));
            mx1 = fmaxf(mx1, __shfl_xor_sync(0xffffffff, mx1, 1));
            mx0 = fmaxf(mx0, __shfl_xor_sync(0xffffffff, mx0, 2));
            mx1 = fmaxf(mx1, __shfl_xor_sync(0xffffffff, mx1, 2));
        };
        auto exp_pack = [&](float& r0, float& r1) {
            const float ms0 = m0 * scale, ms1 = m1 * scale;
            float c0 = 0.f, c1 = 0.f, d0 = 0.f, d1 = 0.f;
#pragma unroll
            for (int j = 0; j < 8; j++) {
                const float e0 = ex2(fmaf(s[4 * j], scale, -ms0)),     e1 = ex2(fmaf(s[4 * j + 1], scale, -ms0));
                const float e2 = ex2(fmaf(s[4 * j + 2], scale, -ms1)), e3 = ex2(fmaf(s[4 * j + 3], scale, -ms1));
                c0 += e0; d0 += e1; c1 += e2; d1 += e3;
                p[2 * j] = pack_bf16(e0, e1); p[2 * j + 1] = pack_bf16(e2, e3);
            }
            r0 = c0 + d0; r1 = c1 + d1;
        };
        mbar_wait(bars + (B_FULL + 0) * 8, 0);
        if (t128_0) TS(22 + wg);
        if (wg != 0) tok_wait(wg);
        wg_fence();
        issue_qk(0);
        tok_pass(nxt);
        wg_wait<0>();
        reg_fence(s);
        if (lane == 0) mbar_arrive(bars + (B_EMPTY + 0) * 8);
        row_max(m0, m1);
        exp_pack(l0, l1);
        slot = 1;
#pragma unroll 1
        for (int i = 0; i < 15; i++) {
            const int ks = slot, kph = ph;
            if (++slot == NSLOT) { slot = 0; ph ^= 1; }
            const int vs = slot, vph = ph;
            if (++slot == NSLOT) { slot = 0; ph ^= 1; }
            TR(i, 0);
            mbar_wait(bars + (B_FULL + ks) * 8, kph);
            TR(i, 1);
            tok_wait(wg);
            TR(i, 2);
            wg_fence();
            issue_qk(ks);
            mbar_wait(bars + (B_FULL + vs) * 8, vph);
            wg_fence();
            issue_pv(vs, i);
            tok_pass(nxt);
            TR(i, 3);
            wg_wait<0>();
            reg_fence(s);
            reg_fence(o);
            TR(i, 4);
            if (lane == 0) { mbar_arrive(bars + (B_EMPTY + ks) * 8); mbar_arrive(bars + (B_EMPTY + vs) * 8); }
            float r0, r1;
            exp_pack(r0, r1);
            TR(i, 5);
            if (__any_sync(0xffffffff, !(fmaxf(r0, r1) <= 65536.f)))
            {
                float mx0, mx1;
                row_max(mx0, mx1);
                mx0 = fmaxf(mx0, m0); mx1 = fmaxf(mx1, m1);
                const float a0 = ex2((m0 - mx0) * scale), a1 = ex2((m1 - mx1) * scale);
                m0 = mx0; m1 = mx1;
                l0 *= a0; l1 *= a1;
#pragma unroll
                for (int j = 0; j < 16; j++) { o[4 * j] *= a0; o[4 * j + 1] *= a0; o[4 * j + 2] *= a1; o[4 * j + 3] *= a1; }
                exp_pack(r0, r1);
            }
            l0 += r0; l1 += r1;
            TR(i, 6);
        }
        mbar_wait(bars + (B_FULL + slot) * 8, ph);
        TR(15, 1);
        tok_wait(wg);
        wg_fence();
        issue_pv(slot, 1);
        if (wg != 2) tok_pass(nxt);
        l0 += __shfl_xor_sync(0xffffffff, l0, 1); l1 += __shfl_xor_sync(0xffffffff, l1, 1);
        l0 += __shfl_xor_sync(0xffffffff, l0, 2); l1 += __shfl_xor_sync(0xffffffff, l1, 2);
        const float i0 = 1.f / l0, i1 = 1.f / l1;
        wg_wait<0>();
        reg_fence(o);
        if (lane == 0) mbar_arrive(bars + (B_EMPTY + slot) * 8);
        if ((tid & 127) == 0) TS(52 + wg);
        {
            const int mi = lane >> 3, r = lane & 7;
            const uint32_t rowa = qa + (warp * 16 + (mi & 1) * 8 + r) * 128;
#pragma unroll
            for (int j = 0; j < 16; j += 2) {
                const uint32_t addr = rowa + (j >> 3) * Q_HALF + ((((j & 7) + (mi >> 1)) ^ r) << 4);
                stsm_x4(addr, pack_bf16(o[4 * j] * i0, o[4 * j + 1] * i0), pack_bf16(o[4 * j + 2] * i1, o[4 * j + 3] * i1),
                        pack_bf16(o[4 * j + 4] * i0, o[4 * j + 5] * i0), pack_bf16(o[4 * j + 6] * i1, o[4 * j + 7] * i1));
            }
        }
        fence_async_smem();
        bar_consumers();

        const int t128 = tid & 127;

        const uint32_t o_lo = (sb + Q_OFF) >> 4;
#pragma unroll 1
        for (int j = wg; j < 9; j += 3) {
            float acc[48];
            const int s0 = (32 + 2 * j) % NSLOT, s1 = (33 + 2 * j) % NSLOT;
            mbar_wait(bars + (B_WOFULL + j) * 8, 0);
            if (j != 0) tok_wait(wg);
            wg_fence();
#pragma unroll
            for (int kk = 0; kk < 16; kk++)
                wgmma_ss_n96<1, 0>(acc, desc(ring_lo + (kk < 8 ? s0 : s1) * (SLOT >> 4) + (kk & 7) * 128),
                                   desc(o_lo + ((kk >> 2) & 1) * (Q_HALF >> 4) + (kk >> 3) * 768 + (kk & 3) * 2), kk != 0);
            wg_commit();
            if (j != 8) tok_pass(nxt);
            wg_wait<0>();
            reg_fence(acc);
            if (lane == 0) mbar_arrive_n(bars + (B_EMPTY + s1) * 8, 3);
            asm volatile("bar.sync %0, 128;" :: "r"(5 + wg) : "memory");
            store_T(acc, sb + RING_OFF + s0 * SLOT, warp, lane);
            fence_async_smem();
            __syncwarp();
            if (lane == 0) mbar_arrive(bars + (B_STAGED + j) * 8);
        }
        if (t128 == 0) TS(56 + wg);
        if (tid == 0) TS(61);
    }
}

typedef CUresult (*EncodeFn)(CUtensorMap*, CUtensorMapDataType, cuuint32_t, void*, const cuuint64_t*, const cuuint64_t*,
                             const cuuint32_t*, const cuuint32_t*, CUtensorMapInterleave, CUtensorMapSwizzle,
                             CUtensorMapL2promotion, CUtensorMapFloatOOBfill);

void encode(EncodeFn fn, CUtensorMap* m, const void* p, int rank, const cuuint64_t* dims, const cuuint64_t* strides,
            const cuuint32_t* box, CUtensorMapL2promotion prom, CUtensorMapSwizzle swz = CU_TENSOR_MAP_SWIZZLE_128B) {
    const cuuint32_t es[3] = {1, 1, 1};
    fn(m, CU_TENSOR_MAP_DATA_TYPE_BFLOAT16, rank, const_cast<void*>(p), dims, strides, box, es,
       CU_TENSOR_MAP_INTERLEAVE_NONE, swz, prom, CU_TENSOR_MAP_FLOAT_OOB_FILL_NONE);
}

}

extern "C" void kernel_launch(void* const* d_in, const int* in_sizes, int n_in, void* d_out, int out_size) {
    (void)in_sizes; (void)n_in; (void)out_size;
    static EncodeFn fn = nullptr;
    if (!fn) {
        void* f = nullptr;
        cudaDriverEntryPointQueryResult q;
        cudaGetDriverEntryPoint("cuTensorMapEncodeTiled", &f, cudaEnableDefault, &q);
        fn = (EncodeFn)f;
        cudaFuncSetAttribute(gqa_fused_kernel, cudaFuncAttributeMaxDynamicSharedMemorySize, SMEM_BYTES);
    }
    const void *x = d_in[0], *k = d_in[1], *v = d_in[2], *wq = d_in[3], *wo = d_in[4];
    CUtensorMap mx, mwq, mk, mv, mwo, mout;
    {
        const cuuint64_t dims[2] = {DM, NB * SQ}, str[1] = {DM * 2};
        const cuuint32_t box[2] = {32, 96}, boxo[2] = {64, 96};
        encode(fn, &mx, x, 2, dims, str, box, CU_TENSOR_MAP_L2_PROMOTION_L2_128B, CU_TENSOR_MAP_SWIZZLE_64B);
        encode(fn, &mout, d_out, 2, dims, str, boxo, CU_TENSOR_MAP_L2_PROMOTION_NONE);
    }
    {
        const cuuint64_t dims[3] = {64, DM, 64}, str[2] = {8192, 128};
        const cuuint32_t box[3] = {64, 32, 4};
        encode(fn, &mwq, wq, 3, dims, str, box, CU_TENSOR_MAP_L2_PROMOTION_L2_128B);
    }
    {
        const cuuint64_t dims[3] = {64, (cuuint64_t)NB * HKV * SK, 2}, str[2] = {256, 128};
        const cuuint32_t box[3] = {64, 64, 2};
        encode(fn, &mk, k, 3, dims, str, box, KV_PROMO);
        encode(fn, &mv, v, 3, dims, str, box, KV_PROMO);
    }
    {
        const cuuint64_t dims[2] = {DM, 4096}, str[1] = {DM * 2};
        const cuuint32_t box[2] = {64, 128};
        encode(fn, &mwo, wo, 2, dims, str, box, CU_TENSOR_MAP_L2_PROMOTION_L2_128B);
    }
    gqa_fused_kernel<<<NB * HKV, NTHREADS, SMEM_BYTES>>>(mx, mwq, mk, mv, mwo, mout, (const char*)x, (const char*)wq, (const char*)k,
                                                         (const char*)v, (const char*)wo, (__nv_bfloat16*)d_out);
}
```

```cpp
#include <cuda_runtime.h>
#include <cuda_bf16.h>
#include <cuda.h>
#include <stdint.h>

namespace {

constexpr int NB = 8, SQ = 96, DM = 576, HKV = 16, SK = 1024;
constexpr int NTHREADS = 512;

constexpr uint32_t Q_OFF    = 0;
constexpr uint32_t Q_HALF   = 192 * 128;
constexpr uint32_t RING_OFF = 2 * Q_HALF;
constexpr uint32_t SLOT     = 16384;
constexpr int      NSLOT    = 11;
constexpr uint32_t BAR_OFF  = RING_OFF + NSLOT * SLOT;
constexpr uint32_t SMEM_BYTES = BAR_OFF + 512 + 1024 + 512;
constexpr uint32_t P1_STAGE = 22528;
constexpr uint32_t P1_XOFF  = 16384;
constexpr int      P1_CH    = DM / 32;
__device__ constexpr uint32_t p1_stage_off(int st) { return st < 2 ? Q_OFF + st * P1_STAGE : BAR_OFF - (4 - st) * P1_STAGE; }
__device__ __forceinline__ uint32_t wo_slot0(int j) { return (uint32_t)(0x64297531aull >> (4 * j)) & 15; }
__device__ __forceinline__ uint32_t wo_slot1(int j) { return (uint32_t)(0x31a086420ull >> (4 * j)) & 15; }
constexpr uint32_t B_P1FULL = 0, B_P1EMPTY = 4, B_FULL = 8, B_EMPTY = 19, B_WOFULL = 30, B_STAGED = 39,
                   B_P1TAIL = 48, B_OH = 49, B_CLEAR = 51, B_CLEARED = 52;

#define KV_T0 50
#define KV_PERIOD 650
constexpr int INFLIGHT0 = 2;
constexpr int INFLIGHT  = 4;
constexpr int SPIN_LIMIT = 1 << 22;

__device__ unsigned g_epoch[NB * HKV];
__device__ unsigned g_cnt[NB * 32];

#define TS(i) do {} while (0)

template <int TA, int TB>
__device__ __forceinline__ void wgmma_ss_n96(float (&d)[48], uint64_t da, uint64_t db, int scale_d) {
    asm volatile("{\n.reg .pred p;\nsetp.ne.b32 p, %50, 0;\n"
        "wgmma.mma_async.sync.aligned.m64n96k16.f32.bf16.bf16 {%0, %1, %2, %3, %4, %5, %6, %7, %8, %9, %10, %11, %12, %13, %14, %15, %16, %17, %18, %19, %20, %21, %22, %23, %24, %25, %26, %27, %28, %29, %30, %31, %32, %33, %34, %35, %36, %37, %38, %39, %40, %41, %42, %43, %44, %45, %46, %47}, %48, %49, p, 1, 1, %51, %52;\n}\n"
        : "+f"(d[0]), "+f"(d[1]), "+f"(d[2]), "+f"(d[3]), "+f"(d[4]), "+f"(d[5]), "+f"(d[6]), "+f"(d[7]), "+f"(d[8]), "+f"(d[9]), "+f"(d[10]), "+f"(d[11]), "+f"(d[12]), "+f"(d[13]), "+f"(d[14]), "+f"(d[15]), "+f"(d[16]), "+f"(d[17]), "+f"(d[18]), "+f"(d[19]), "+f"(d[20]), "+f"(d[21]), "+f"(d[22]), "+f"(d[23]), "+f"(d[24]), "+f"(d[25]), "+f"(d[26]), "+f"(d[27]), "+f"(d[28]), "+f"(d[29]), "+f"(d[30]), "+f"(d[31]), "+f"(d[32]), "+f"(d[33]), "+f"(d[34]), "+f"(d[35]), "+f"(d[36]), "+f"(d[37]), "+f"(d[38]), "+f"(d[39]), "+f"(d[40]), "+f"(d[41]), "+f"(d[42]), "+f"(d[43]), "+f"(d[44]), "+f"(d[45]), "+f"(d[46]), "+f"(d[47])
        : "l"(da), "l"(db), "r"(scale_d), "n"(TA), "n"(TB));
}
template <int TA, int TB>
__device__ __forceinline__ void wgmma_ss_n64(float (&d)[32], uint64_t da, uint64_t db, int scale_d) {
    asm volatile("{\n.reg .pred p;\nsetp.ne.b32 p, %34, 0;\n"
        "wgmma.mma_async.sync.aligned.m64n64k16.f32.bf16.bf16 {%0, %1, %2, %3, %4, %5, %6, %7, %8, %9, %10, %11, %12, %13, %14, %15, %16, %17, %18, %19, %20, %21, %22, %23, %24, %25, %26, %27, %28, %29, %30, %31}, %32, %33, p, 1, 1, %35, %36;\n}\n"
        : "+f"(d[0]), "+f"(d[1]), "+f"(d[2]), "+f"(d[3]), "+f"(d[4]), "+f"(d[5]), "+f"(d[6]), "+f"(d[7]), "+f"(d[8]), "+f"(d[9]), "+f"(d[10]), "+f"(d[11]), "+f"(d[12]), "+f"(d[13]), "+f"(d[14]), "+f"(d[15]), "+f"(d[16]), "+f"(d[17]), "+f"(d[18]), "+f"(d[19]), "+f"(d[20]), "+f"(d[21]), "+f"(d[22]), "+f"(d[23]), "+f"(d[24]), "+f"(d[25]), "+f"(d[26]), "+f"(d[27]), "+f"(d[28]), "+f"(d[29]), "+f"(d[30]), "+f"(d[31])
        : "l"(da), "l"(db), "r"(scale_d), "n"(TA), "n"(TB));
}
template <int TB>
__device__ __forceinline__ void wgmma_rs_n128(float (&d)[64], uint32_t a0, uint32_t a1, uint32_t a2, uint32_t a3, uint64_t db, int scale_d) {
    asm volatile("{\n.reg .pred p;\nsetp.ne.b32 p, %69, 0;\n"
        "wgmma.mma_async.sync.aligned.m64n128k16.f32.bf16.bf16 {%0, %1, %2, %3, %4, %5, %6, %7, %8, %9, %10, %11, %12, %13, %14, %15, %16, %17, %18, %19, %20, %21, %22, %23, %24, %25, %26, %27, %28, %29, %30, %31, %32, %33, %34, %35, %36, %37, %38, %39, %40, %41, %42, %43, %44, %45, %46, %47, %48, %49, %50, %51, %52, %53, %54, %55, %56, %57, %58, %59, %60, %61, %62, %63}, {%64, %65, %66, %67}, %68, p, 1, 1, %70;\n}\n"
        : "+f"(d[0]), "+f"(d[1]), "+f"(d[2]), "+f"(d[3]), "+f"(d[4]), "+f"(d[5]), "+f"(d[6]), "+f"(d[7]), "+f"(d[8]), "+f"(d[9]), "+f"(d[10]), "+f"(d[11]), "+f"(d[12]), "+f"(d[13]), "+f"(d[14]), "+f"(d[15]), "+f"(d[16]), "+f"(d[17]), "+f"(d[18]), "+f"(d[19]), "+f"(d[20]), "+f"(d[21]), "+f"(d[22]), "+f"(d[23]), "+f"(d[24]), "+f"(d[25]), "+f"(d[26]), "+f"(d[27]), "+f"(d[28]), "+f"(d[29]), "+f"(d[30]), "+f"(d[31]), "+f"(d[32]), "+f"(d[33]), "+f"(d[34]), "+f"(d[35]), "+f"(d[36]), "+f"(d[37]), "+f"(d[38]), "+f"(d[39]), "+f"(d[40]), "+f"(d[41]), "+f"(d[42]), "+f"(d[43]), "+f"(d[44]), "+f"(d[45]), "+f"(d[46]), "+f"(d[47]), "+f"(d[48]), "+f"(d[49]), "+f"(d[50]), "+f"(d[51]), "+f"(d[52]), "+f"(d[53]), "+f"(d[54]), "+f"(d[55]), "+f"(d[56]), "+f"(d[57]), "+f"(d[58]), "+f"(d[59]), "+f"(d[60]), "+f"(d[61]), "+f"(d[62]), "+f"(d[63])
        : "r"(a0), "r"(a1), "r"(a2), "r"(a3), "l"(db), "r"(scale_d), "n"(TB));
}

__device__ __forceinline__ void wg_fence()  { asm volatile("wgmma.fence.sync.aligned;" ::: "memory"); }
__device__ __forceinline__ void wg_commit() { asm volatile("wgmma.commit_group.sync.aligned;" ::: "memory"); }
template <int N> __device__ __forceinline__ void wg_wait() { asm volatile("wgmma.wait_group.sync.aligned %0;" :: "n"(N) : "memory"); }
template <int N> __device__ __forceinline__ void reg_fence(float (&d)[N]) {
#pragma unroll
    for (int i = 0; i < N; i++) asm volatile("" : "+f"(d[i]) :: "memory");
}
__device__ __forceinline__ uint64_t desc(uint32_t lo)   { return ((uint64_t)((1024u >> 4) | (1u << 30)) << 32) | lo; }
__device__ __forceinline__ uint64_t desc64(uint32_t lo) { return ((uint64_t)((512u >> 4) | (2u << 30)) << 32) | lo; }

__device__ __forceinline__ void mbar_init(uint32_t bar, uint32_t cnt) { asm volatile("mbarrier.init.shared::cta.b64 [%0], %1;" :: "r"(bar), "r"(cnt) : "memory"); }
__device__ __forceinline__ void mbar_expect_tx(uint32_t bar, uint32_t bytes) { asm volatile("mbarrier.arrive.expect_tx.shared::cta.b64 _, [%0], %1;" :: "r"(bar), "r"(bytes) : "memory"); }
__device__ __forceinline__ void mbar_arrive(uint32_t bar) { asm volatile("mbarrier.arrive.shared::cta.b64 _, [%0];" :: "r"(bar) : "memory"); }
__device__ __forceinline__ void mbar_arrive_n(uint32_t bar, uint32_t n) { asm volatile("mbarrier.arrive.shared::cta.b64 _, [%0], %1;" :: "r"(bar), "r"(n) : "memory"); }
__device__ __forceinline__ void mbar_wait(uint32_t bar, uint32_t parity) {
    asm volatile("{\n.reg .pred p;\n.reg .u32 c;\nmov.u32 c, 0;\n"
                 "WAIT_LOOP:\nmbarrier.try_wait.parity.shared::cta.b64 p, [%0], %1;\n@p bra WAIT_DONE;\n"
                 "add.u32 c, c, 1;\nsetp.lt.u32 p, c, 4194304;\n@p bra WAIT_LOOP;\ntrap;\nWAIT_DONE:\n}" :: "r"(bar), "r"(parity) : "memory");
}
__device__ __forceinline__ void tma2d(uint32_t dst, const CUtensorMap* m, int c0, int c1, uint32_t bar) {
    asm volatile("cp.async.bulk.tensor.2d.shared::cluster.global.mbarrier::complete_tx::bytes [%0], [%1, {%3, %4}], [%2];"
                 :: "r"(dst), "l"(m), "r"(bar), "r"(c0), "r"(c1) : "memory");
}
__device__ __forceinline__ void tma3d(uint32_t dst, const CUtensorMap* m, int c0, int c1, int c2, uint32_t bar) {
    asm volatile("cp.async.bulk.tensor.3d.shared::cluster.global.mbarrier::complete_tx::bytes [%0], [%1, {%3, %4, %5}], [%2];"
                 :: "r"(dst), "l"(m), "r"(bar), "r"(c0), "r"(c1), "r"(c2) : "memory");
}
__device__ __forceinline__ void tma3d_hint(uint32_t dst, const CUtensorMap* m, int c0, int c1, int c2, uint32_t bar, uint64_t pol) {
    asm volatile("cp.async.bulk.tensor.3d.shared::cluster.global.mbarrier::complete_tx::bytes.L2::cache_hint [%0], [%1, {%3, %4, %5}], [%2], %6;"
                 :: "r"(dst), "l"(m), "r"(bar), "r"(c0), "r"(c1), "r"(c2), "l"(pol) : "memory");
}
__device__ __forceinline__ void tma2d_reduce_add(const CUtensorMap* m, int c0, int c1, uint32_t src) {
    asm volatile("cp.reduce.async.bulk.tensor.2d.global.shared::cta.add.tile.bulk_group [%0, {%2, %3}], [%1];"
                 :: "l"(m), "r"(src), "r"(c0), "r"(c1) : "memory");
}
__device__ __forceinline__ void prefetch_map(const CUtensorMap* m) { asm volatile("prefetch.tensormap [%0];" :: "l"(m) : "memory"); }
__device__ __forceinline__ void prefetch_l2(const void* p) { asm volatile("prefetch.global.L2 [%0];" :: "l"(p)); }
__device__ __forceinline__ uint32_t time_ns() { uint32_t t; asm volatile("mov.u32 %0, %%globaltimer_lo;" : "=r"(t)); return t; }
__device__ __forceinline__ void fence_async_smem() { asm volatile("fence.proxy.async.shared::cta;" ::: "memory"); }
__device__ __forceinline__ void tok_wait(int me) { asm volatile("bar.sync %0, 256;" :: "r"(me + 2) : "memory"); }
__device__ __forceinline__ void tok_pass(int to) { asm volatile("bar.arrive %0, 256;" :: "r"(to + 2) : "memory"); }
__device__ __forceinline__ uint32_t pack_bf16(float lo, float hi) {
    uint32_t r; asm("cvt.rn.bf16x2.f32 %0, %1, %2;" : "=r"(r) : "f"(hi), "f"(lo)); return r;
}
__device__ __forceinline__ void stsm_x4(uint32_t addr, uint32_t a, uint32_t b, uint32_t c, uint32_t d) {
    asm volatile("stmatrix.sync.aligned.m8n8.x4.shared.b16 [%0], {%1, %2, %3, %4};" :: "r"(addr), "r"(a), "r"(b), "r"(c), "r"(d) : "memory");
}
__device__ __forceinline__ void stsm_x4_t(uint32_t addr, uint32_t a, uint32_t b, uint32_t c, uint32_t d) {
    asm volatile("stmatrix.sync.aligned.m8n8.x4.trans.shared.b16 [%0], {%1, %2, %3, %4};" :: "r"(addr), "r"(a), "r"(b), "r"(c), "r"(d) : "memory");
}
__device__ __forceinline__ float ex2(float x) { float r; asm("ex2.approx.ftz.f32 %0, %1;" : "=f"(r) : "f"(x)); return r; }
__device__ __forceinline__ bool elect_one() {
    uint32_t p; asm volatile("{\n.reg .pred p;\nelect.sync _|p, 0xffffffff;\nselp.b32 %0, 1, 0, p;\n}" : "=r"(p)); return p;
}

__device__ __forceinline__ void store_T(const float (&acc)[48], uint32_t base, int warp, int lane) {
    const int mi = lane >> 3, r = lane & 7;
    base += ((mi >> 1) * 8 + r) * 128 + (((2 * warp + (mi & 1)) ^ r) << 4);
#pragma unroll
    for (int j = 0; j < 12; j += 2)
        stsm_x4_t(base + j * 1024, pack_bf16(acc[4 * j], acc[4 * j + 1]), pack_bf16(acc[4 * j + 2], acc[4 * j + 3]),
                  pack_bf16(acc[4 * j + 4], acc[4 * j + 5]), pack_bf16(acc[4 * j + 6], acc[4 * j + 7]));
}

template <int NT>
__device__ __forceinline__ void phase1(uint32_t sb, uint32_t bars, int t0, int t1, int warp, int lane, long long t_start) {
    float acc0[48], acc1[48];
#pragma unroll 1
    for (int c = 0; c < P1_CH; c++) {
        const int st = c & 3;
        mbar_wait(bars + (B_P1FULL + st) * 8, (c >> 2) & 1);
        if (NT == 2 && threadIdx.x == 0 && !(c & 1)) TS(26 + (c >> 1));
        const uint32_t ws = (sb + p1_stage_off(st)) >> 4, xs = ws + (P1_XOFF >> 4);
        wg_fence();
#pragma unroll
        for (int kk = 0; kk < 2; kk++) {
            const uint64_t db = desc64(xs + kk * 2);
            wgmma_ss_n96<1, 0>(acc0, desc(ws + t0 * 256 + kk * 128), db, (c | kk) != 0);
            if (NT == 2) wgmma_ss_n96<1, 0>(acc1, desc(ws + t1 * 256 + kk * 128), db, (c | kk) != 0);
        }
        wg_commit();
        wg_wait<1>();
        if (c > 0 && lane == 0) mbar_arrive(bars + (c == 16 ? B_P1TAIL : B_P1EMPTY + ((c - 1) & 3)) * 8);
    }
    wg_wait<0>();
    reg_fence(acc0);
    if (NT == 2) reg_fence(acc1);
    if (lane == 0) mbar_arrive(bars + (B_P1EMPTY + 1) * 8);
    mbar_wait(bars + (B_P1EMPTY + 0) * 8, 0);
    mbar_wait(bars + (B_P1EMPTY + 1) * 8, 0);
    store_T(acc0, sb + Q_OFF + (t0 & 1) * Q_HALF + (t0 >> 1) * 12288, warp, lane);
    if (NT == 2) store_T(acc1, sb + Q_OFF + (t1 & 1) * Q_HALF + (t1 >> 1) * 12288, warp, lane);
}

__global__ void __launch_bounds__(NTHREADS, 1)
gqa_fused_kernel(const __grid_constant__ CUtensorMap map_x, const __grid_constant__ CUtensorMap map_wq,
                 const __grid_constant__ CUtensorMap map_k, const __grid_constant__ CUtensorMap map_v,
                 const __grid_constant__ CUtensorMap map_wo, const __grid_constant__ CUtensorMap map_out,
                 const char* __restrict__ gx, const char* __restrict__ gwq, __nv_bfloat16* __restrict__ out) {
    extern __shared__ __align__(1024) unsigned char smem_raw[];
    long long t_start = 0;
    uint32_t sb;
    asm volatile("mov.u32 %0, %1;" : "=r"(sb) : "r"(((uint32_t)__cvta_generic_to_shared(smem_raw) + 1023) & ~1023u));
    const uint32_t bars = sb + BAR_OFF;
    const int tid = threadIdx.x, lane = tid & 31;
    const int wg = __shfl_sync(0xffffffff, tid >> 7, 0);
    const int warp = __shfl_sync(0xffffffff, (tid >> 5) & 3, 0);
    const int b = blockIdx.x & 7, h = blockIdx.x >> 3;

    auto load_p1 = [&](int c) {
        const uint32_t fb = bars + (B_P1FULL + (c & 3)) * 8, dst = sb + p1_stage_off(c & 3);
        mbar_expect_tx(fb, P1_STAGE);
        tma3d(dst, &map_wq, 0, c * 32, h * 4, fb);
        tma2d(dst + P1_XOFF, &map_x, c * 32, b * SQ, fb);
    };
    if (tid == 384) {
        prefetch_map(&map_wq); prefetch_map(&map_x);
#pragma unroll
        for (int i = 0; i < 4; i++) mbar_init(bars + (B_P1FULL + i) * 8, 1);
        fence_async_smem();
#pragma unroll
        for (int c = 0; c < 4; c++) load_p1(c);
    } else if (tid == 416) {
        prefetch_map(&map_k); prefetch_map(&map_v);
#pragma unroll
        for (int i = 0; i < NSLOT; i++) { mbar_init(bars + (B_FULL + i) * 8, 1); mbar_init(bars + (B_EMPTY + i) * 8, 12); }
        fence_async_smem();
    } else if (tid == 0) {
#pragma unroll
        for (int i = 0; i < 4; i++) mbar_init(bars + (B_P1EMPTY + i) * 8, 12);
#pragma unroll
        for (int i = 0; i < 9; i++) { mbar_init(bars + (B_WOFULL + i) * 8, 2); mbar_init(bars + (B_STAGED + i) * 8, 4); }
        mbar_init(bars + B_P1TAIL * 8, 12);
        mbar_init(bars + B_OH * 8, 6); mbar_init(bars + (B_OH + 1) * 8, 6);
        mbar_init(bars + B_CLEAR * 8, 1); mbar_init(bars + B_CLEARED * 8, 1);
        fence_async_smem();
    }
    __syncthreads();

    if (wg == 3) {
        asm volatile("setmaxnreg.dec.sync.aligned.u32 80;");
        auto issue_reds = [&](int j0) {
            prefetch_map(&map_out);
            mbar_wait(bars + B_CLEARED * 8, 0);
            asm volatile("fence.proxy.async.global;" ::: "memory");
#pragma unroll 1
            for (int j = j0; j < 9; j += 2) {
                mbar_wait(bars + (B_STAGED + j) * 8, 0);
                tma2d_reduce_add(&map_out, j * 64, b * SQ, sb + RING_OFF + wo_slot0(j) * SLOT);
                asm volatile("cp.async.bulk.commit_group;" ::: "memory");
                TS(2 + j);
                if (j < 3) {
                    asm volatile("cp.async.bulk.wait_group.read 0;" ::: "memory");
                    mbar_arrive_n(bars + (B_EMPTY + wo_slot0(j)) * 8, 12);
                }
            }
            asm volatile("cp.async.bulk.wait_group.read 0;" ::: "memory");
        };
        if (warp == 0) {
#pragma unroll 1
            for (int c = 4; c < P1_CH; c++) {
                mbar_wait(bars + (B_P1EMPTY + (c & 3)) * 8, ((c >> 2) - 1) & 1);
                if (elect_one()) load_p1(c);
                __syncwarp();
            }
            if (lane == 0) issue_reds(0);
        } else if (warp == 1) {
            const int kvrow = (b * HKV + h) * SK;
            mbar_wait(bars + (B_P1FULL + 3) * 8, 0);
            if (elect_one()) {
                const uint32_t t0 = time_ns();
                uint64_t pol;
                asm volatile("createpolicy.fractional.L2::evict_first.b64 %0, 1.0;" : "=l"(pol));
                const uint32_t ring = sb + RING_OFF;
                int now = 0, tnext = KV_T0;
                auto pace = [&]() {
                    while (now < tnext) { now = time_ns() - t0; if (now < tnext) __nanosleep(32); }
                    tnext += KV_PERIOD;
                };
                auto kv_load = [&](const CUtensorMap* m, int row, uint32_t slot) {
                    const uint32_t fb = bars + B_FULL * 8 + slot * 8;
                    mbar_expect_tx(fb, SLOT);
                    tma3d_hint(ring + slot * SLOT, m, 0, row, 0, fb, pol);
                };
#pragma unroll
                for (int u = 0; u < NSLOT; u++) {
                    pace();
                    if (u >= (u < 8 ? INFLIGHT0 : INFLIGHT)) mbar_wait(bars + (B_FULL + u - (u < 8 ? INFLIGHT0 : INFLIGHT)) * 8, 0);
                    if (u == 8) mbar_wait(bars + B_P1TAIL * 8, 0);
                    const bool isv = u != 0 && !(u & 1);
                    kv_load(isv ? &map_v : &map_k, kvrow + (isv ? (u >> 1) - 1 : (u + 1) >> 1) * 64, u);
                }
                uint32_t slot = 0, ph = 0;
                uint32_t fslot = NSLOT - INFLIGHT, fph = 0;
                auto landed = [&]() {
                    mbar_wait(bars + B_FULL * 8 + fslot * 8, fph);
                    if (++fslot == NSLOT) { fslot = 0; fph ^= 1; }
                };
                auto next_unit = [&](const CUtensorMap* m, int row) {
                    pace();
                    landed();
                    mbar_wait(bars + B_EMPTY * 8 + slot * 8, ph);
                    kv_load(m, row, slot);
                    if (++slot == NSLOT) { slot = 0; ph ^= 1; }
                };
                int row = kvrow + 5 * 64;
#pragma unroll 1
                for (int i = 5; i < 15; i++) {
                    next_unit(&map_k, row + 64);
                    next_unit(&map_v, row);
                    row += 64;
                    if (i == 10) mbar_arrive(bars + B_CLEAR * 8);
                }
                next_unit(&map_v, row);
                prefetch_map(&map_wo);
                landed();
#pragma unroll 1
                for (int j = 0; j < 9; j++) {
                    const uint32_t fb = bars + B_WOFULL * 8 + j * 8;
                    const uint32_t s0 = wo_slot0(j), s1 = wo_slot1(j);
                    mbar_wait(bars + B_EMPTY * 8 + s0 * 8, (j > 5) ^ (s0 == 10));
                    mbar_expect_tx(fb, SLOT); tma2d(ring + s0 * SLOT, &map_wo, j * 64, h * 256, fb);
                    mbar_wait(bars + B_EMPTY * 8 + s1 * 8, (j >= 5) ^ (s1 == 10));
                    mbar_expect_tx(fb, SLOT); tma2d(ring + s1 * SLOT, &map_wo, j * 64, h * 256 + 128, fb);
                }
                TS(51);
            }
        } else {
            const int t = tid - 448;
            if (t < 38) {
                const char* pw = gwq + (size_t)(8 * b + (t >> 2)) * 8192 + h * 512 + (t & 3) * 128;
                const char* px = gx + (size_t)(b * SQ + 6 * h + (t - 32)) * (DM * 2);
#pragma unroll
                for (int kb = 0; kb < 9; kb++) prefetch_l2(t < 32 ? pw + (size_t)kb * 64 * 8192 : px + kb * 128);
            }
            const uint32_t epoch = g_epoch[blockIdx.x] + 1;
            mbar_wait(bars + B_CLEAR * 8, 0);
            uint4* o4 = reinterpret_cast<uint4*>(out + (size_t)(b * SQ + 6 * h) * DM);
            for (int i = t; i < 6 * DM / 8; i += 64) o4[i] = make_uint4(0, 0, 0, 0);
            __threadfence();
            asm volatile("bar.sync 8, 64;" ::: "memory");
            if (t == 32) {
                atomicAdd(&g_cnt[b * 32], 1);
                unsigned cur; int it = 0;
                do { asm volatile("ld.acquire.gpu.global.u32 %0, [%1];" : "=r"(cur) : "l"(&g_cnt[b * 32]) : "memory"); __nanosleep(100); }
                while ((int)(cur - epoch * HKV) < 0 && ++it < SPIN_LIMIT);
                mbar_arrive(bars + B_CLEARED * 8);
                g_epoch[blockIdx.x] = epoch;
            }
            if (t == 0) issue_reds(1);
        }
    } else {
        asm volatile("setmaxnreg.inc.sync.aligned.u32 144;");
        if (wg == 0) phase1<2>(sb, bars, 0, 3, warp, lane, t_start);
        else         phase1<1>(sb, bars, wg, 0, warp, lane, t_start);
        fence_async_smem();
        asm volatile("bar.sync 1, 384;" ::: "memory");
        if (tid == 0) TS(1);

        const float scale = 0.08838834764831845f * 1.4426950408889634f;
        float o[64], s[32];
        uint32_t p[16];
        float m0, m1, l0, l1;
        const uint32_t qa = sb + Q_OFF + wg * 8192;
        const uint32_t q_lo = qa >> 4, ring_lo = (sb + RING_OFF) >> 4;
        const int nxt = wg == 2 ? 0 : wg + 1;
        int slot = 0, ph = 0;
        auto advance = [&]() { if (++slot == NSLOT) { slot = 0; ph ^= 1; } };
        auto issue_qk = [&](int sl) {
            const uint32_t k_lo = ring_lo + sl * (SLOT >> 4);
#pragma unroll
            for (int kk = 0; kk < 8; kk++)
                wgmma_ss_n64<0, 0>(s, desc(q_lo + (kk >> 2) * (Q_HALF >> 4) + (kk & 3) * 2), desc(k_lo + (kk >> 2) * 512 + (kk & 3) * 2), kk != 0);
            wg_commit();
        };
        auto issue_pv = [&](int sl, int accum) {
            const uint32_t v_lo = (ring_lo + sl * (SLOT >> 4)) | ((8192u >> 4) << 16);
#pragma unroll
            for (int kk = 0; kk < 4; kk++)
                wgmma_rs_n128<1>(o, p[4 * kk], p[4 * kk + 1], p[4 * kk + 2], p[4 * kk + 3], desc(v_lo + kk * 128), kk == 0 ? accum : 1);
            wg_commit();
        };
        auto row_max = [&](float& mx0, float& mx1) {
            float a0 = fmaxf(s[0], s[1]), a1 = fmaxf(s[2], s[3]), b0 = fmaxf(s[4], s[5]), b1 = fmaxf(s[6], s[7]);
#pragma unroll
            for (int j = 2; j < 8; j += 2) {
                a0 = fmaxf(a0, fmaxf(s[4 * j], s[4 * j + 1]));     a1 = fmaxf(a1, fmaxf(s[4 * j + 2], s[4 * j + 3]));
                b0 = fmaxf(b0, fmaxf(s[4 * j + 4], s[4 * j + 5])); b1 = fmaxf(b1, fmaxf(s[4 * j + 6], s[4 * j + 7]));
            }
            mx0 = fmaxf(a0, b0); mx1 = fmaxf(a1, b1);
            mx0 = fmaxf(mx0, __shfl_xor_sync(0xffffffff, mx0, 1));
            mx1 = fmaxf(mx1, __shfl_xor_sync(0xffffffff, mx1, 1));
            mx0 = fmaxf(mx0, __shfl_xor_sync(0xffffffff, mx0, 2));
            mx1 = fmaxf(mx1, __shfl_xor_sync(0xffffffff, mx1, 2));
        };
        auto exp_pack = [&](float& r0, float& r1) {
            const float ms0 = m0 * scale, ms1 = m1 * scale;
            float c0 = 0.f, c1 = 0.f, d0 = 0.f, d1 = 0.f;
#pragma unroll
            for (int j = 0; j < 8; j++) {
                const float e0 = ex2(fmaf(s[4 * j], scale, -ms0)),     e1 = ex2(fmaf(s[4 * j + 1], scale, -ms0));
                const float e2 = ex2(fmaf(s[4 * j + 2], scale, -ms1)), e3 = ex2(fmaf(s[4 * j + 3], scale, -ms1));
                c0 += e0; d0 += e1; c1 += e2; d1 += e3;
                p[2 * j] = pack_bf16(e0, e1); p[2 * j + 1] = pack_bf16(e2, e3);
            }
            r0 = c0 + d0; r1 = c1 + d1;
        };
        mbar_wait(bars + (B_FULL + 0) * 8, 0);
        if (wg != 0) tok_wait(wg);
        wg_fence();
        issue_qk(0);
        tok_pass(nxt);
        wg_wait<0>();
        reg_fence(s);
        if (lane == 0) mbar_arrive(bars + (B_EMPTY + 0) * 8);
        row_max(m0, m1);
        exp_pack(l0, l1);
        slot = 1;
#pragma unroll 1
        for (int i = 0; i < 14; i++) {
            const int ks = slot, kph = ph;
            advance();
            const int vs = slot, vph = ph;
            advance();
            mbar_wait(bars + (B_FULL + ks) * 8, kph);
            tok_wait(wg);
            wg_fence();
            issue_qk(ks);
            mbar_wait(bars + (B_FULL + vs) * 8, vph);
            wg_fence();
            issue_pv(vs, i);
            tok_pass(nxt);
            wg_wait<1>();
            if (lane == 0) mbar_arrive(bars + (B_EMPTY + ks) * 8);
            wg_wait<0>();
            reg_fence(s);
            reg_fence(o);
            if ((tid & 127) == 0 && wg != 1) TS((wg == 2 ? 96 : 112) + i);
            if (lane == 0) mbar_arrive(bars + (B_EMPTY + vs) * 8);
            float r0, r1;
            exp_pack(r0, r1);
            if (__any_sync(0xffffffff, !(fmaxf(r0, r1) <= 65536.f))) {
                float mx0, mx1;
                row_max(mx0, mx1);
                mx0 = fmaxf(mx0, m0); mx1 = fmaxf(mx1, m1);
                const float a0 = ex2((m0 - mx0) * scale), a1 = ex2((m1 - mx1) * scale);
                m0 = mx0; m1 = mx1;
                l0 *= a0; l1 *= a1;
#pragma unroll
                for (int j = 0; j < 16; j++) { o[4 * j] *= a0; o[4 * j + 1] *= a0; o[4 * j + 2] *= a1; o[4 * j + 3] *= a1; }
                exp_pack(r0, r1);
            }
            l0 += r0; l1 += r1;
        }
        {
            mbar_wait(bars + (B_FULL + slot) * 8, ph);
            tok_wait(wg);
            wg_fence();
            issue_qk(slot);
            tok_pass(nxt);
            wg_wait<0>();
            reg_fence(s);
            if (lane == 0) mbar_arrive(bars + (B_EMPTY + slot) * 8);
            advance();
            float mx0, mx1;
            row_max(mx0, mx1);
            mx0 = fmaxf(mx0, m0); mx1 = fmaxf(mx1, m1);
            float a0 = ex2((m0 - mx0) * scale), a1 = ex2((m1 - mx1) * scale);
            const float ms0 = mx0 * scale, ms1 = mx1 * scale;
            float c0 = 0.f, c1 = 0.f, d0 = 0.f, d1 = 0.f;
#pragma unroll
            for (int j = 0; j < 8; j++) {
                s[4 * j]     = ex2(fmaf(s[4 * j], scale, -ms0));     s[4 * j + 1] = ex2(fmaf(s[4 * j + 1], scale, -ms0));
                s[4 * j + 2] = ex2(fmaf(s[4 * j + 2], scale, -ms1)); s[4 * j + 3] = ex2(fmaf(s[4 * j + 3], scale, -ms1));
                c0 += s[4 * j]; d0 += s[4 * j + 1]; c1 += s[4 * j + 2]; d1 += s[4 * j + 3];
            }
            l0 = l0 * a0 + (c0 + d0); l1 = l1 * a1 + (c1 + d1);
            l0 += __shfl_xor_sync(0xffffffff, l0, 1); l1 += __shfl_xor_sync(0xffffffff, l1, 1);
            l0 += __shfl_xor_sync(0xffffffff, l0, 2); l1 += __shfl_xor_sync(0xffffffff, l1, 2);
            const float i0 = __frcp_rn(l0), i1 = __frcp_rn(l1);
            a0 *= i0; a1 *= i1;
#pragma unroll
            for (int j = 0; j < 8; j++) { s[4 * j] *= i0; s[4 * j + 1] *= i0; s[4 * j + 2] *= i1; s[4 * j + 3] *= i1; }
            reg_fence(s);
            mbar_wait(bars + (B_FULL + slot) * 8, ph);
            tok_wait(wg);
            wg_fence();
            issue_pv(slot, 1);
            tok_pass(nxt);
            wg_wait<0>();
            reg_fence(o);
            if (lane == 0) mbar_arrive(bars + (B_EMPTY + slot) * 8);
            advance();
#pragma unroll
            for (int j = 0; j < 16; j++) p[j] = pack_bf16(s[2 * j], s[2 * j + 1]);
#pragma unroll
            for (int j = 0; j < 16; j++) { o[4 * j] *= a0; o[4 * j + 1] *= a0; o[4 * j + 2] *= a1; o[4 * j + 3] *= a1; }
            mbar_wait(bars + (B_FULL + slot) * 8, ph);
            if (tid == 0) TS(21);
            tok_wait(wg);
            wg_fence();
            issue_pv(slot, 1);
            if (wg != 2) tok_pass(nxt);
            wg_wait<0>();
            reg_fence(o);
            if (lane == 0) mbar_arrive(bars + (B_EMPTY + slot) * 8);
        }
        if ((tid & 127) == 0) TS(52 + wg);
        {
            const int mi = lane >> 3, r = lane & 7;
            const uint32_t rowa = qa + (warp * 16 + (mi & 1) * 8 + r) * 128;
#pragma unroll
            for (int j = 0; j < 16; j += 2) {
                const uint32_t addr = rowa + (j >> 3) * Q_HALF + ((((j & 7) + (mi >> 1)) ^ r) << 4);
                stsm_x4(addr, pack_bf16(o[4 * j], o[4 * j + 1]), pack_bf16(o[4 * j + 2], o[4 * j + 3]),
                        pack_bf16(o[4 * j + 4], o[4 * j + 5]), pack_bf16(o[4 * j + 6], o[4 * j + 7]));
            }
        }
        fence_async_smem();
        __syncwarp();
        if (lane == 0) mbar_arrive(bars + (B_OH + (wg * 4 + warp >= 6)) * 8);

        const uint32_t o_lo = (sb + Q_OFF) >> 4;
#pragma unroll 1
        for (int j = wg; j < 9; j += 3) {
            float acc[48];
            const uint32_t s0 = wo_slot0(j), s1 = wo_slot1(j);
            mbar_wait(bars + (B_WOFULL + j) * 8, 0);
            mbar_wait(bars + B_OH * 8, 0);
            if (j != 0) tok_wait(wg);
            wg_fence();
#pragma unroll
            for (int kk = 0; kk < 8; kk++)
                wgmma_ss_n96<1, 0>(acc, desc(ring_lo + s0 * (SLOT >> 4) + kk * 128),
                                   desc(o_lo + (kk >> 2) * (Q_HALF >> 4) + (kk & 3) * 2), kk != 0);
            mbar_wait(bars + (B_OH + 1) * 8, 0);
            wg_fence();
#pragma unroll
            for (int kk = 0; kk < 8; kk++)
                wgmma_ss_n96<1, 0>(acc, desc(ring_lo + s1 * (SLOT >> 4) + kk * 128),
                                   desc(o_lo + (kk >> 2) * (Q_HALF >> 4) + 768 + (kk & 3) * 2), 1);
            wg_commit();
            if (j != 8) tok_pass(nxt);
            wg_wait<0>();
            reg_fence(acc);
            if (lane == 0 && j < 4) mbar_arrive_n(bars + (B_EMPTY + s1) * 8, 3);
            asm volatile("bar.sync %0, 128;" :: "r"(5 + wg) : "memory");
            store_T(acc, sb + RING_OFF + s0 * SLOT, warp, lane);
            fence_async_smem();
            __syncwarp();
            if (lane == 0) mbar_arrive(bars + (B_STAGED + j) * 8);
        }
    }
}

typedef CUresult (*EncodeFn)(CUtensorMap*, CUtensorMapDataType, cuuint32_t, void*, const cuuint64_t*, const cuuint64_t*,
                             const cuuint32_t*, const cuuint32_t*, CUtensorMapInterleave, CUtensorMapSwizzle,
                             CUtensorMapL2promotion, CUtensorMapFloatOOBfill);

void encode(EncodeFn fn, CUtensorMap* m, const void* p, int rank, const cuuint64_t* dims, const cuuint64_t* strides,
            const cuuint32_t* box, CUtensorMapL2promotion prom, CUtensorMapSwizzle swz = CU_TENSOR_MAP_SWIZZLE_128B) {
    const cuuint32_t es[3] = {1, 1, 1};
    fn(m, CU_TENSOR_MAP_DATA_TYPE_BFLOAT16, rank, const_cast<void*>(p), dims, strides, box, es,
       CU_TENSOR_MAP_INTERLEAVE_NONE, swz, prom, CU_TENSOR_MAP_FLOAT_OOB_FILL_NONE);
}

}

extern "C" void kernel_launch(void* const* d_in, const int* in_sizes, int n_in, void* d_out, int out_size) {
    (void)in_sizes; (void)n_in; (void)out_size;
    static EncodeFn fn = nullptr;
    if (!fn) {
        void* f = nullptr;
        cudaDriverEntryPointQueryResult q;
        cudaGetDriverEntryPoint("cuTensorMapEncodeTiled", &f, cudaEnableDefault, &q);
        fn = (EncodeFn)f;
        cudaFuncSetAttribute(gqa_fused_kernel, cudaFuncAttributeMaxDynamicSharedMemorySize, SMEM_BYTES);
    }
    const void *x = d_in[0], *k = d_in[1], *v = d_in[2], *wq = d_in[3], *wo = d_in[4];
    CUtensorMap mx, mwq, mk, mv, mwo, mout;
    {
        const cuuint64_t dims[2] = {DM, NB * SQ}, str[1] = {DM * 2};
        const cuuint32_t box[2] = {32, SQ}, boxo[2] = {64, SQ};
        encode(fn, &mx, x, 2, dims, str, box, CU_TENSOR_MAP_L2_PROMOTION_L2_128B, CU_TENSOR_MAP_SWIZZLE_64B);
        encode(fn, &mout, d_out, 2, dims, str, boxo, CU_TENSOR_MAP_L2_PROMOTION_NONE);
    }
    {
        const cuuint64_t dims[3] = {64, DM, 64}, str[2] = {8192, 128};
        const cuuint32_t box[3] = {64, 32, 4};
        encode(fn, &mwq, wq, 3, dims, str, box, CU_TENSOR_MAP_L2_PROMOTION_L2_128B);
    }
    {
        const cuuint64_t dims[3] = {64, (cuuint64_t)NB * HKV * SK, 2}, str[2] = {256, 128};
        const cuuint32_t box[3] = {64, 64, 2};
        encode(fn, &mk, k, 3, dims, str, box, CU_TENSOR_MAP_L2_PROMOTION_L2_128B);
        encode(fn, &mv, v, 3, dims, str, box, CU_TENSOR_MAP_L2_PROMOTION_L2_128B);
    }
    {
        const cuuint64_t dims[2] = {DM, 4096}, str[1] = {DM * 2};
        const cuuint32_t box[2] = {64, 128};
        encode(fn, &mwo, wo, 2, dims, str, box, CU_TENSOR_MAP_L2_PROMOTION_L2_128B);
    }
    gqa_fused_kernel<<<NB * HKV, NTHREADS, SMEM_BYTES>>>(mx, mwq, mk, mv, mwo, mout, (const char*)x, (const char*)wq,
                                                         (__nv_bfloat16*)d_out);
}
```

```cpp
#include <cuda_runtime.h>
#include <cuda_bf16.h>
#include <cuda.h>
#include <stdint.h>


namespace {

constexpr int NB = 8, SQ = 96, DM = 576, HKV = 16, SK = 1024;
constexpr int NTHREADS = 512;

constexpr uint32_t Q_OFF    = 0;
constexpr uint32_t Q_HALF   = 192 * 128;
constexpr uint32_t RING_OFF = 2 * Q_HALF;
constexpr uint32_t SLOT     = 16384;
constexpr int      NSLOT    = 11;
constexpr uint32_t BAR_OFF  = RING_OFF + NSLOT * SLOT;
constexpr uint32_t SMEM_BYTES = BAR_OFF + 512 + 1024;
constexpr uint32_t P1_STAGE = 22528;
constexpr uint32_t P1_XOFF  = 16384;
constexpr int      P1_CH    = DM / 32;
__device__ constexpr uint32_t p1_stage_off(int st) { return st < 2 ? Q_OFF + st * P1_STAGE : BAR_OFF - (4 - st) * P1_STAGE; }
__device__ __forceinline__ uint32_t wo_slot0(int j) { return (uint32_t)(0x64297531aull >> (4 * j)) & 15; }
__device__ __forceinline__ uint32_t wo_slot1(int j) { return (uint32_t)(0x31a086420ull >> (4 * j)) & 15; }
constexpr uint32_t B_P1FULL = 0, B_P1EMPTY = 4, B_FULL = 8, B_EMPTY = 19, B_WOFULL = 30, B_STAGED = 39,
                   B_P1TAIL = 48, B_OH = 49, B_CLEAR = 51, B_CLEARED = 52;

constexpr int KV_PERIOD0 = 700;
constexpr int KV_PERIOD  = 650;
constexpr int INFLIGHT0  = 2;
constexpr int INFLIGHT   = 4;
constexpr int PF_GAP     = 650;
constexpr int CREGS      = 152;
constexpr int SPIN_LIMIT = 1 << 22;

__device__ unsigned g_epoch[NB * HKV];
__device__ unsigned g_cnt[NB * 32];


template <int TA, int TB>
__device__ __forceinline__ void wgmma_ss_n96(float (&d)[48], uint64_t da, uint64_t db, int scale_d) {
    asm volatile("{\n.reg .pred p;\nsetp.ne.b32 p, %50, 0;\n"
        "wgmma.mma_async.sync.aligned.m64n96k16.f32.bf16.bf16 {%0, %1, %2, %3, %4, %5, %6, %7, %8, %9, %10, %11, %12, %13, %14, %15, %16, %17, %18, %19, %20, %21, %22, %23, %24, %25, %26, %27, %28, %29, %30, %31, %32, %33, %34, %35, %36, %37, %38, %39, %40, %41, %42, %43, %44, %45, %46, %47}, %48, %49, p, 1, 1, %51, %52;\n}\n"
        : "+f"(d[0]), "+f"(d[1]), "+f"(d[2]), "+f"(d[3]), "+f"(d[4]), "+f"(d[5]), "+f"(d[6]), "+f"(d[7]), "+f"(d[8]), "+f"(d[9]), "+f"(d[10]), "+f"(d[11]), "+f"(d[12]), "+f"(d[13]), "+f"(d[14]), "+f"(d[15]), "+f"(d[16]), "+f"(d[17]), "+f"(d[18]), "+f"(d[19]), "+f"(d[20]), "+f"(d[21]), "+f"(d[22]), "+f"(d[23]), "+f"(d[24]), "+f"(d[25]), "+f"(d[26]), "+f"(d[27]), "+f"(d[28]), "+f"(d[29]), "+f"(d[30]), "+f"(d[31]), "+f"(d[32]), "+f"(d[33]), "+f"(d[34]), "+f"(d[35]), "+f"(d[36]), "+f"(d[37]), "+f"(d[38]), "+f"(d[39]), "+f"(d[40]), "+f"(d[41]), "+f"(d[42]), "+f"(d[43]), "+f"(d[44]), "+f"(d[45]), "+f"(d[46]), "+f"(d[47])
        : "l"(da), "l"(db), "r"(scale_d), "n"(TA), "n"(TB));
}
template <int TA, int TB>
__device__ __forceinline__ void wgmma_ss_n64(float (&d)[32], uint64_t da, uint64_t db, int scale_d) {
    asm volatile("{\n.reg .pred p;\nsetp.ne.b32 p, %34, 0;\n"
        "wgmma.mma_async.sync.aligned.m64n64k16.f32.bf16.bf16 {%0, %1, %2, %3, %4, %5, %6, %7, %8, %9, %10, %11, %12, %13, %14, %15, %16, %17, %18, %19, %20, %21, %22, %23, %24, %25, %26, %27, %28, %29, %30, %31}, %32, %33, p, 1, 1, %35, %36;\n}\n"
        : "+f"(d[0]), "+f"(d[1]), "+f"(d[2]), "+f"(d[3]), "+f"(d[4]), "+f"(d[5]), "+f"(d[6]), "+f"(d[7]), "+f"(d[8]), "+f"(d[9]), "+f"(d[10]), "+f"(d[11]), "+f"(d[12]), "+f"(d[13]), "+f"(d[14]), "+f"(d[15]), "+f"(d[16]), "+f"(d[17]), "+f"(d[18]), "+f"(d[19]), "+f"(d[20]), "+f"(d[21]), "+f"(d[22]), "+f"(d[23]), "+f"(d[24]), "+f"(d[25]), "+f"(d[26]), "+f"(d[27]), "+f"(d[28]), "+f"(d[29]), "+f"(d[30]), "+f"(d[31])
        : "l"(da), "l"(db), "r"(scale_d), "n"(TA), "n"(TB));
}
template <int TB>
__device__ __forceinline__ void wgmma_rs_n128(float (&d)[64], uint32_t a0, uint32_t a1, uint32_t a2, uint32_t a3, uint64_t db, int scale_d) {
    asm volatile("{\n.reg .pred p;\nsetp.ne.b32 p, %69, 0;\n"
        "wgmma.mma_async.sync.aligned.m64n128k16.f32.bf16.bf16 {%0, %1, %2, %3, %4, %5, %6, %7, %8, %9, %10, %11, %12, %13, %14, %15, %16, %17, %18, %19, %20, %21, %22, %23, %24, %25, %26, %27, %28, %29, %30, %31, %32, %33, %34, %35, %36, %37, %38, %39, %40, %41, %42, %43, %44, %45, %46, %47, %48, %49, %50, %51, %52, %53, %54, %55, %56, %57, %58, %59, %60, %61, %62, %63}, {%64, %65, %66, %67}, %68, p, 1, 1, %70;\n}\n"
        : "+f"(d[0]), "+f"(d[1]), "+f"(d[2]), "+f"(d[3]), "+f"(d[4]), "+f"(d[5]), "+f"(d[6]), "+f"(d[7]), "+f"(d[8]), "+f"(d[9]), "+f"(d[10]), "+f"(d[11]), "+f"(d[12]), "+f"(d[13]), "+f"(d[14]), "+f"(d[15]), "+f"(d[16]), "+f"(d[17]), "+f"(d[18]), "+f"(d[19]), "+f"(d[20]), "+f"(d[21]), "+f"(d[22]), "+f"(d[23]), "+f"(d[24]), "+f"(d[25]), "+f"(d[26]), "+f"(d[27]), "+f"(d[28]), "+f"(d[29]), "+f"(d[30]), "+f"(d[31]), "+f"(d[32]), "+f"(d[33]), "+f"(d[34]), "+f"(d[35]), "+f"(d[36]), "+f"(d[37]), "+f"(d[38]), "+f"(d[39]), "+f"(d[40]), "+f"(d[41]), "+f"(d[42]), "+f"(d[43]), "+f"(d[44]), "+f"(d[45]), "+f"(d[46]), "+f"(d[47]), "+f"(d[48]), "+f"(d[49]), "+f"(d[50]), "+f"(d[51]), "+f"(d[52]), "+f"(d[53]), "+f"(d[54]), "+f"(d[55]), "+f"(d[56]), "+f"(d[57]), "+f"(d[58]), "+f"(d[59]), "+f"(d[60]), "+f"(d[61]), "+f"(d[62]), "+f"(d[63])
        : "r"(a0), "r"(a1), "r"(a2), "r"(a3), "l"(db), "r"(scale_d), "n"(TB));
}


__device__ __forceinline__ void wg_fence()  { asm volatile("wgmma.fence.sync.aligned;" ::: "memory"); }
__device__ __forceinline__ void wg_commit() { asm volatile("wgmma.commit_group.sync.aligned;" ::: "memory"); }
template <int N> __device__ __forceinline__ void wg_wait() { asm volatile("wgmma.wait_group.sync.aligned %0;" :: "n"(N) : "memory"); }
template <int N> __device__ __forceinline__ void reg_fence(float (&d)[N]) {
#pragma unroll
    for (int i = 0; i < N; i++) asm volatile("" : "+f"(d[i]) :: "memory");
}
__device__ __forceinline__ uint64_t desc(uint32_t lo)   { return ((uint64_t)((1024u >> 4) | (1u << 30)) << 32) | lo; }
__device__ __forceinline__ uint64_t desc64(uint32_t lo) { return ((uint64_t)((512u >> 4) | (2u << 30)) << 32) | lo; }

__device__ __forceinline__ void mbar_init(uint32_t bar, uint32_t cnt) { asm volatile("mbarrier.init.shared::cta.b64 [%0], %1;" :: "r"(bar), "r"(cnt) : "memory"); }
__device__ __forceinline__ void mbar_expect_tx(uint32_t bar, uint32_t bytes) { asm volatile("mbarrier.arrive.expect_tx.shared::cta.b64 _, [%0], %1;" :: "r"(bar), "r"(bytes) : "memory"); }
__device__ __forceinline__ void mbar_arrive(uint32_t bar) { asm volatile("mbarrier.arrive.shared::cta.b64 _, [%0];" :: "r"(bar) : "memory"); }
__device__ __forceinline__ void mbar_arrive_n(uint32_t bar, uint32_t n) { asm volatile("mbarrier.arrive.shared::cta.b64 _, [%0], %1;" :: "r"(bar), "r"(n) : "memory"); }
__device__ __forceinline__ void mbar_wait(uint32_t bar, uint32_t parity) {
    asm volatile("{\n.reg .pred p;\n.reg .u32 c;\nmov.u32 c, 0;\n"
                 "WAIT_LOOP:\nmbarrier.try_wait.parity.shared::cta.b64 p, [%0], %1;\n@p bra WAIT_DONE;\n"
                 "add.u32 c, c, 1;\nsetp.lt.u32 p, c, 4194304;\n@p bra WAIT_LOOP;\ntrap;\nWAIT_DONE:\n}" :: "r"(bar), "r"(parity) : "memory");
}
__device__ __forceinline__ void tma2d(uint32_t dst, const CUtensorMap* m, int c0, int c1, uint32_t bar) {
    asm volatile("cp.async.bulk.tensor.2d.shared::cluster.global.mbarrier::complete_tx::bytes [%0], [%1, {%3, %4}], [%2];"
                 :: "r"(dst), "l"(m), "r"(bar), "r"(c0), "r"(c1) : "memory");
}
__device__ __forceinline__ void tma3d(uint32_t dst, const CUtensorMap* m, int c0, int c1, int c2, uint32_t bar) {
    asm volatile("cp.async.bulk.tensor.3d.shared::cluster.global.mbarrier::complete_tx::bytes [%0], [%1, {%3, %4, %5}], [%2];"
                 :: "r"(dst), "l"(m), "r"(bar), "r"(c0), "r"(c1), "r"(c2) : "memory");
}
__device__ __forceinline__ void tma3d_hint(uint32_t dst, const CUtensorMap* m, int c0, int c1, int c2, uint32_t bar, uint64_t pol) {
    asm volatile("cp.async.bulk.tensor.3d.shared::cluster.global.mbarrier::complete_tx::bytes.L2::cache_hint [%0], [%1, {%3, %4, %5}], [%2], %6;"
                 :: "r"(dst), "l"(m), "r"(bar), "r"(c0), "r"(c1), "r"(c2), "l"(pol) : "memory");
}
__device__ __forceinline__ void tma2d_reduce_add(const CUtensorMap* m, int c0, int c1, uint32_t src) {
    asm volatile("cp.reduce.async.bulk.tensor.2d.global.shared::cta.add.tile.bulk_group [%0, {%2, %3}], [%1];"
                 :: "l"(m), "r"(src), "r"(c0), "r"(c1) : "memory");
}
__device__ __forceinline__ void prefetch_map(const CUtensorMap* m) { asm volatile("prefetch.tensormap [%0];" :: "l"(m) : "memory"); }
__device__ __forceinline__ void prefetch_l2(const void* p) { asm volatile("prefetch.global.L2 [%0];" :: "l"(p)); }
__device__ __forceinline__ uint32_t time_ns() { uint32_t t; asm volatile("mov.u32 %0, %%globaltimer_lo;" : "=r"(t)); return t; }
__device__ __forceinline__ void fence_async_smem() { asm volatile("fence.proxy.async.shared::cta;" ::: "memory"); }
__device__ __forceinline__ void tok_wait(int me) { asm volatile("bar.sync %0, 256;" :: "r"(me + 2) : "memory"); }
__device__ __forceinline__ void tok_pass(int to) { asm volatile("bar.arrive %0, 256;" :: "r"(to + 2) : "memory"); }
__device__ __forceinline__ uint32_t pack_bf16(float lo, float hi) {
    uint32_t r; asm("cvt.rn.bf16x2.f32 %0, %1, %2;" : "=r"(r) : "f"(hi), "f"(lo)); return r;
}
__device__ __forceinline__ void stsm_x4(uint32_t addr, uint32_t a, uint32_t b, uint32_t c, uint32_t d) {
    asm volatile("stmatrix.sync.aligned.m8n8.x4.shared.b16 [%0], {%1, %2, %3, %4};" :: "r"(addr), "r"(a), "r"(b), "r"(c), "r"(d) : "memory");
}
__device__ __forceinline__ void stsm_x4_t(uint32_t addr, uint32_t a, uint32_t b, uint32_t c, uint32_t d) {
    asm volatile("stmatrix.sync.aligned.m8n8.x4.trans.shared.b16 [%0], {%1, %2, %3, %4};" :: "r"(addr), "r"(a), "r"(b), "r"(c), "r"(d) : "memory");
}
__device__ __forceinline__ float ex2(float x) { float r; asm("ex2.approx.ftz.f32 %0, %1;" : "=f"(r) : "f"(x)); return r; }
__device__ __forceinline__ bool elect_one() {
    uint32_t p; asm volatile("{\n.reg .pred p;\nelect.sync _|p, 0xffffffff;\nselp.b32 %0, 1, 0, p;\n}" : "=r"(p)); return p;
}

__device__ __forceinline__ void store_T(const float (&acc)[48], uint32_t base, int warp, int lane) {
    const int mi = lane >> 3, r = lane & 7;
    base += ((mi >> 1) * 8 + r) * 128 + (((2 * warp + (mi & 1)) ^ r) << 4);
#pragma unroll
    for (int j = 0; j < 12; j += 2)
        stsm_x4_t(base + j * 1024, pack_bf16(acc[4 * j], acc[4 * j + 1]), pack_bf16(acc[4 * j + 2], acc[4 * j + 3]),
                  pack_bf16(acc[4 * j + 4], acc[4 * j + 5]), pack_bf16(acc[4 * j + 6], acc[4 * j + 7]));
}

template <int NT>
__device__ __forceinline__ void phase1(uint32_t sb, uint32_t bars, int t0, int t1, int warp, int lane) {
    float acc0[48], acc1[48];
#pragma unroll 1
    for (int c = 0; c < P1_CH; c++) {
        const int st = c & 3;
        mbar_wait(bars + (B_P1FULL + st) * 8, (c >> 2) & 1);
        const uint32_t ws = (sb + p1_stage_off(st)) >> 4, xs = ws + (P1_XOFF >> 4);
        wg_fence();
#pragma unroll
        for (int kk = 0; kk < 2; kk++) {
            const uint64_t db = desc64(xs + kk * 2);
            wgmma_ss_n96<1, 0>(acc0, desc(ws + t0 * 256 + kk * 128), db, (c | kk) != 0);
            if (NT == 2) wgmma_ss_n96<1, 0>(acc1, desc(ws + t1 * 256 + kk * 128), db, (c | kk) != 0);
        }
        wg_commit();
        wg_wait<1>();
        if (c > 0 && lane == 0) mbar_arrive(bars + (c == 16 ? B_P1TAIL : B_P1EMPTY + ((c - 1) & 3)) * 8);
    }
    wg_wait<0>();
    reg_fence(acc0);
    if (NT == 2) reg_fence(acc1);
    if (lane == 0) mbar_arrive(bars + (B_P1EMPTY + 1) * 8);
    mbar_wait(bars + (B_P1EMPTY + 0) * 8, 0);
    mbar_wait(bars + (B_P1EMPTY + 1) * 8, 0);
    store_T(acc0, sb + Q_OFF + (t0 & 1) * Q_HALF + (t0 >> 1) * 12288, warp, lane);
    if (NT == 2) store_T(acc1, sb + Q_OFF + (t1 & 1) * Q_HALF + (t1 >> 1) * 12288, warp, lane);
}

__global__ void __launch_bounds__(NTHREADS, 1)
gqa_fused_kernel(const __grid_constant__ CUtensorMap map_x, const __grid_constant__ CUtensorMap map_wq,
                 const __grid_constant__ CUtensorMap map_k, const __grid_constant__ CUtensorMap map_v,
                 const __grid_constant__ CUtensorMap map_wo, const __grid_constant__ CUtensorMap map_out,
                 const char* __restrict__ gx, const char* __restrict__ gwq, __nv_bfloat16* __restrict__ out) {
    extern __shared__ __align__(1024) unsigned char smem_raw[];
    uint32_t sb;
    asm volatile("mov.u32 %0, %1;" : "=r"(sb) : "r"(((uint32_t)__cvta_generic_to_shared(smem_raw) + 1023) & ~1023u));
    const uint32_t bars = sb + BAR_OFF;
    const int tid = threadIdx.x, lane = tid & 31;
    const int wg = __shfl_sync(0xffffffff, tid >> 7, 0);
    const int warp = __shfl_sync(0xffffffff, (tid >> 5) & 3, 0);
    const int b = blockIdx.x & 7, h = blockIdx.x >> 3;

    auto load_p1 = [&](int c) {
        const uint32_t fb = bars + (B_P1FULL + (c & 3)) * 8, dst = sb + p1_stage_off(c & 3);
        mbar_expect_tx(fb, P1_STAGE);
        tma3d(dst, &map_wq, 0, c * 32, h * 4, fb);
        tma2d(dst + P1_XOFF, &map_x, c * 32, b * SQ, fb);
    };
    if (tid == 384) {
        prefetch_map(&map_wq); prefetch_map(&map_x);
#pragma unroll
        for (int i = 0; i < 4; i++) mbar_init(bars + (B_P1FULL + i) * 8, 1);
        fence_async_smem();
#pragma unroll
        for (int c = 0; c < 4; c++) load_p1(c);
    } else if (tid == 416) {
        prefetch_map(&map_k); prefetch_map(&map_v);
#pragma unroll
        for (int i = 0; i < NSLOT; i++) { mbar_init(bars + (B_FULL + i) * 8, 1); mbar_init(bars + (B_EMPTY + i) * 8, 12); }
        fence_async_smem();
    } else if (tid == 0) {
#pragma unroll
        for (int i = 0; i < 4; i++) mbar_init(bars + (B_P1EMPTY + i) * 8, 12);
#pragma unroll
        for (int i = 0; i < 9; i++) { mbar_init(bars + (B_WOFULL + i) * 8, 2); mbar_init(bars + (B_STAGED + i) * 8, 4); }
        mbar_init(bars + B_P1TAIL * 8, 12);
        mbar_init(bars + B_OH * 8, 6); mbar_init(bars + (B_OH + 1) * 8, 6);
        mbar_init(bars + B_CLEAR * 8, 1); mbar_init(bars + B_CLEARED * 8, 1);
        fence_async_smem();
    }
    if (tid < 448) {
        __syncwarp();
        if (tid < 32 || tid >= 384) asm volatile("bar.arrive 9, 160;" ::: "memory");
        asm volatile("bar.sync 0, 448;" ::: "memory");
    }

    if (wg == 3) {
        asm volatile("setmaxnreg.dec.sync.aligned.u32 %0;" :: "n"(512 - 3 * CREGS));
        auto issue_reds = [&](int j0) {
            prefetch_map(&map_out);
            mbar_wait(bars + B_CLEARED * 8, 0);
            asm volatile("fence.proxy.async.global;" ::: "memory");
#pragma unroll 1
            for (int j = j0; j < 9; j += 2) {
                mbar_wait(bars + (B_STAGED + j) * 8, 0);
                tma2d_reduce_add(&map_out, j * 64, b * SQ, sb + RING_OFF + wo_slot0(j) * SLOT);
                asm volatile("cp.async.bulk.commit_group;" ::: "memory");
                if (j < 3) {
                    asm volatile("cp.async.bulk.wait_group.read 0;" ::: "memory");
                    mbar_arrive_n(bars + (B_EMPTY + wo_slot0(j)) * 8, 12);
                }
            }
            asm volatile("cp.async.bulk.wait_group.read 0;" ::: "memory");
        };
        if (warp == 0) {
#pragma unroll 1
            for (int c = 4; c < P1_CH; c++) {
                mbar_wait(bars + (B_P1EMPTY + (c & 3)) * 8, ((c >> 2) - 1) & 1);
                if (elect_one()) load_p1(c);
                __syncwarp();
            }
            if (lane == 0) issue_reds(0);
        } else if (warp == 1) {
            const int kvrow = (b * HKV + h) * SK;
            mbar_wait(bars + B_P1FULL * 8, 0);
            if (elect_one()) {
                const uint32_t t0 = time_ns();
                uint64_t pol;
                asm volatile("createpolicy.fractional.L2::evict_first.b64 %0, 1.0;" : "=l"(pol));
                const uint32_t ring = sb + RING_OFF;
                int now = 0, tnext = 0, spins = 0;
                auto pace = [&](int period) {
                    while (now < tnext) { now = time_ns() - t0; if (now < tnext) { __nanosleep(32); if (++spins > 65536) break; } }
                    tnext += period;
                };
                auto kv_load = [&](const CUtensorMap* m, int row, uint32_t slot) {
                    const uint32_t fb = bars + B_FULL * 8 + slot * 8;
                    mbar_expect_tx(fb, SLOT);
                    tma3d_hint(ring + slot * SLOT, m, 0, row, 0, fb, pol);
                };
#pragma unroll
                for (int u = 0; u < NSLOT; u++) {
                    pace(u < 8 ? KV_PERIOD0 : KV_PERIOD);
                    const int depth = u < 8 ? INFLIGHT0 : INFLIGHT;
                    if (u >= depth) mbar_wait(bars + (B_FULL + u - depth) * 8, 0);
                    if (u == 8) mbar_wait(bars + B_P1TAIL * 8, 0);
                    const bool isv = u != 0 && !(u & 1);
                    kv_load(isv ? &map_v : &map_k, kvrow + (isv ? (u >> 1) - 1 : (u + 1) >> 1) * 64, u);
                }
                uint32_t slot = 0, ph = 0;
                uint32_t fslot = NSLOT - INFLIGHT, fph = 0;
                auto landed = [&]() {
                    mbar_wait(bars + B_FULL * 8 + fslot * 8, fph);
                    if (++fslot == NSLOT) { fslot = 0; fph ^= 1; }
                };
                auto next_unit = [&](const CUtensorMap* m, int row) {
                    pace(KV_PERIOD);
                    landed();
                    mbar_wait(bars + B_EMPTY * 8 + slot * 8, ph);
                    kv_load(m, row, slot);
                    if (++slot == NSLOT) { slot = 0; ph ^= 1; }
                };
                int row = kvrow + 5 * 64;
#pragma unroll 1
                for (int i = 5; i < 15; i++) {
                    next_unit(&map_k, row + 64);
                    next_unit(&map_v, row);
                    row += 64;
                    if (i == 10) mbar_arrive(bars + B_CLEAR * 8);
                }
                next_unit(&map_v, row);
                prefetch_map(&map_wo);
                landed();
#pragma unroll 1
                for (int j = 0; j < 9; j++) {
                    const uint32_t fb = bars + B_WOFULL * 8 + j * 8;
                    const uint32_t s0 = wo_slot0(j), s1 = wo_slot1(j);
                    mbar_wait(bars + B_EMPTY * 8 + s0 * 8, (j > 5) ^ (s0 == 10));
                    mbar_expect_tx(fb, SLOT); tma2d(ring + s0 * SLOT, &map_wo, j * 64, h * 256, fb);
                    mbar_wait(bars + B_EMPTY * 8 + s1 * 8, (j >= 5) ^ (s1 == 10));
                    mbar_expect_tx(fb, SLOT); tma2d(ring + s1 * SLOT, &map_wo, j * 64, h * 256 + 128, fb);
                }
            }
        } else {
            const int t = tid - 448;
            if (t < 38) {
                const char* pw = gwq + (size_t)(8 * b + (t >> 2)) * 8192 + h * 512 + (t & 3) * 128;
                const char* px = gx + (size_t)(b * SQ + 6 * h + (t - 32)) * (DM * 2);
#pragma unroll
                for (int kb = 0; kb < 9; kb++) {
                    prefetch_l2(t < 32 ? pw + (size_t)kb * 64 * 8192 : px + kb * 128);
                    if (kb >= 3 && kb < 8) {
                        const uint32_t tq = time_ns();
                        for (int it = 0; (int)(time_ns() - tq) < PF_GAP && it < 1024; it++) __nanosleep(32);
                    }
                }
            }
            __syncwarp();
            asm volatile("bar.sync 9, 160;" ::: "memory");
            const uint32_t epoch = g_epoch[blockIdx.x] + 1;
            mbar_wait(bars + B_CLEAR * 8, 0);
            uint4* o4 = reinterpret_cast<uint4*>(out + (size_t)(b * SQ + 6 * h) * DM);
            for (int i = t; i < 6 * DM / 8; i += 64) o4[i] = make_uint4(0, 0, 0, 0);
            __threadfence();
            __syncwarp();
            asm volatile("bar.sync 8, 64;" ::: "memory");
            if (t == 32) {
                atomicAdd(&g_cnt[b * 32], 1);
                unsigned cur; int it = 0;
                do { asm volatile("ld.acquire.gpu.global.u32 %0, [%1];" : "=r"(cur) : "l"(&g_cnt[b * 32]) : "memory"); __nanosleep(100); }
                while ((int)(cur - epoch * HKV) < 0 && ++it < SPIN_LIMIT);
                mbar_arrive(bars + B_CLEARED * 8);
                g_epoch[blockIdx.x] = epoch;
            }
            if (t == 0) issue_reds(1);
        }
    } else {
        asm volatile("setmaxnreg.inc.sync.aligned.u32 %0;" :: "n"(CREGS));
        if (wg == 0) phase1<2>(sb, bars, 0, 3, warp, lane);
        else         phase1<1>(sb, bars, wg, 0, warp, lane);
        fence_async_smem();
        asm volatile("bar.sync 1, 384;" ::: "memory");

        const float scale = 0.08838834764831845f * 1.4426950408889634f;
        float o[64], s[32];
        uint32_t p[16];
        float m0, m1, l0, l1;
        const uint32_t qa = sb + Q_OFF + wg * 8192;
        const uint32_t q_lo = qa >> 4, ring_lo = (sb + RING_OFF) >> 4;
        const int nxt = wg == 2 ? 0 : wg + 1;
        int slot = 0, ph = 0;
        auto advance = [&]() { if (++slot == NSLOT) { slot = 0; ph ^= 1; } };
        auto issue_qk = [&](int sl) {
            const uint32_t k_lo = ring_lo + sl * (SLOT >> 4);
#pragma unroll
            for (int kk = 0; kk < 8; kk++)
                wgmma_ss_n64<0, 0>(s, desc(q_lo + (kk >> 2) * (Q_HALF >> 4) + (kk & 3) * 2), desc(k_lo + (kk >> 2) * 512 + (kk & 3) * 2), kk != 0);
            wg_commit();
        };
        auto issue_pv = [&](int sl, int accum) {
            const uint32_t v_lo = (ring_lo + sl * (SLOT >> 4)) | ((8192u >> 4) << 16);
#pragma unroll
            for (int kk = 0; kk < 4; kk++)
                wgmma_rs_n128<1>(o, p[4 * kk], p[4 * kk + 1], p[4 * kk + 2], p[4 * kk + 3], desc(v_lo + kk * 128), kk == 0 ? accum : 1);
            wg_commit();
        };
        auto row_max = [&](float& mx0, float& mx1) {
            float a0 = fmaxf(s[0], s[1]), a1 = fmaxf(s[2], s[3]), b0 = fmaxf(s[4], s[5]), b1 = fmaxf(s[6], s[7]);
#pragma unroll
            for (int j = 2; j < 8; j += 2) {
                a0 = fmaxf(a0, fmaxf(s[4 * j], s[4 * j + 1]));     a1 = fmaxf(a1, fmaxf(s[4 * j + 2], s[4 * j + 3]));
                b0 = fmaxf(b0, fmaxf(s[4 * j + 4], s[4 * j + 5])); b1 = fmaxf(b1, fmaxf(s[4 * j + 6], s[4 * j + 7]));
            }
            mx0 = fmaxf(a0, b0); mx1 = fmaxf(a1, b1);
            mx0 = fmaxf(mx0, __shfl_xor_sync(0xffffffff, mx0, 1));
            mx1 = fmaxf(mx1, __shfl_xor_sync(0xffffffff, mx1, 1));
            mx0 = fmaxf(mx0, __shfl_xor_sync(0xffffffff, mx0, 2));
            mx1 = fmaxf(mx1, __shfl_xor_sync(0xffffffff, mx1, 2));
        };
        auto exp_pack = [&](float& r0, float& r1) {
            const float ms0 = m0 * scale, ms1 = m1 * scale;
            float c0 = 0.f, c1 = 0.f, d0 = 0.f, d1 = 0.f;
#pragma unroll
            for (int j = 0; j < 8; j++) {
                const float e0 = ex2(fmaf(s[4 * j], scale, -ms0)),     e1 = ex2(fmaf(s[4 * j + 1], scale, -ms0));
                const float e2 = ex2(fmaf(s[4 * j + 2], scale, -ms1)), e3 = ex2(fmaf(s[4 * j + 3], scale, -ms1));
                c0 += e0; d0 += e1; c1 += e2; d1 += e3;
                p[2 * j] = pack_bf16(e0, e1); p[2 * j + 1] = pack_bf16(e2, e3);
            }
            r0 = c0 + d0; r1 = c1 + d1;
        };
        auto softmax_step = [&]() {
            float r0, r1;
            exp_pack(r0, r1);
            if (__any_sync(0xffffffff, !(fmaxf(r0, r1) <= 65536.f))) {
                float mx0, mx1;
                row_max(mx0, mx1);
                mx0 = fmaxf(mx0, m0); mx1 = fmaxf(mx1, m1);
                const float a0 = ex2((m0 - mx0) * scale), a1 = ex2((m1 - mx1) * scale);
                m0 = mx0; m1 = mx1;
                l0 *= a0; l1 *= a1;
#pragma unroll
                for (int j = 0; j < 16; j++) { o[4 * j] *= a0; o[4 * j + 1] *= a0; o[4 * j + 2] *= a1; o[4 * j + 3] *= a1; }
                exp_pack(r0, r1);
            }
            l0 += r0; l1 += r1;
        };
        mbar_wait(bars + (B_FULL + 0) * 8, 0);
        if (wg != 0) tok_wait(wg);
        wg_fence();
        issue_qk(0);
        tok_pass(nxt);
        wg_wait<0>();
        reg_fence(s);
        if (lane == 0) mbar_arrive(bars + (B_EMPTY + 0) * 8);
        row_max(m0, m1);
        exp_pack(l0, l1);
        slot = 1;
#pragma unroll 1
        for (int i = 0; i < 14; i++) {
            const int ks = slot, kph = ph;
            advance();
            const int vs = slot, vph = ph;
            advance();
            mbar_wait(bars + (B_FULL + ks) * 8, kph);
            tok_wait(wg);
            wg_fence();
            issue_qk(ks);
            mbar_wait(bars + (B_FULL + vs) * 8, vph);
            wg_fence();
            issue_pv(vs, i);
            tok_pass(nxt);
            wg_wait<1>();
            if (lane == 0) mbar_arrive(bars + (B_EMPTY + ks) * 8);
            wg_wait<0>();
            reg_fence(s);
            reg_fence(o);
            if (lane == 0) mbar_arrive(bars + (B_EMPTY + vs) * 8);
            softmax_step();
        }
        {
            mbar_wait(bars + (B_FULL + slot) * 8, ph);
            tok_wait(wg);
            wg_fence();
            issue_qk(slot);
            tok_pass(nxt);
            wg_wait<0>();
            reg_fence(s);
            if (lane == 0) mbar_arrive(bars + (B_EMPTY + slot) * 8);
            advance();
            float mx0, mx1;
            row_max(mx0, mx1);
            mx0 = fmaxf(mx0, m0); mx1 = fmaxf(mx1, m1);
            float a0 = ex2((m0 - mx0) * scale), a1 = ex2((m1 - mx1) * scale);
            const float ms0 = mx0 * scale, ms1 = mx1 * scale;
            float c0 = 0.f, c1 = 0.f, d0 = 0.f, d1 = 0.f;
#pragma unroll
            for (int j = 0; j < 8; j++) {
                s[4 * j]     = ex2(fmaf(s[4 * j], scale, -ms0));     s[4 * j + 1] = ex2(fmaf(s[4 * j + 1], scale, -ms0));
                s[4 * j + 2] = ex2(fmaf(s[4 * j + 2], scale, -ms1)); s[4 * j + 3] = ex2(fmaf(s[4 * j + 3], scale, -ms1));
                c0 += s[4 * j]; d0 += s[4 * j + 1]; c1 += s[4 * j + 2]; d1 += s[4 * j + 3];
            }
            l0 = l0 * a0 + (c0 + d0); l1 = l1 * a1 + (c1 + d1);
            l0 += __shfl_xor_sync(0xffffffff, l0, 1); l1 += __shfl_xor_sync(0xffffffff, l1, 1);
            l0 += __shfl_xor_sync(0xffffffff, l0, 2); l1 += __shfl_xor_sync(0xffffffff, l1, 2);
            const float i0 = __frcp_rn(l0), i1 = __frcp_rn(l1);
            a0 *= i0; a1 *= i1;
#pragma unroll
            for (int j = 0; j < 8; j++) { s[4 * j] *= i0; s[4 * j + 1] *= i0; s[4 * j + 2] *= i1; s[4 * j + 3] *= i1; }
            reg_fence(s);
            mbar_wait(bars + (B_FULL + slot) * 8, ph);
            tok_wait(wg);
            wg_fence();
            issue_pv(slot, 1);
            tok_pass(nxt);
            wg_wait<0>();
            reg_fence(o);
            if (lane == 0) mbar_arrive(bars + (B_EMPTY + slot) * 8);
            advance();
#pragma unroll
            for (int j = 0; j < 16; j++) p[j] = pack_bf16(s[2 * j], s[2 * j + 1]);
#pragma unroll
            for (int j = 0; j < 16; j++) { o[4 * j] *= a0; o[4 * j + 1] *= a0; o[4 * j + 2] *= a1; o[4 * j + 3] *= a1; }
            mbar_wait(bars + (B_FULL + slot) * 8, ph);
            tok_wait(wg);
            wg_fence();
            issue_pv(slot, 1);
            if (wg != 2) tok_pass(nxt);
            wg_wait<0>();
            reg_fence(o);
            if (lane == 0) mbar_arrive(bars + (B_EMPTY + slot) * 8);
        }
        {
            const int mi = lane >> 3, r = lane & 7;
            const uint32_t rowa = qa + (warp * 16 + (mi & 1) * 8 + r) * 128;
#pragma unroll
            for (int j = 0; j < 16; j += 2) {
                const uint32_t addr = rowa + (j >> 3) * Q_HALF + ((((j & 7) + (mi >> 1)) ^ r) << 4);
                stsm_x4(addr, pack_bf16(o[4 * j], o[4 * j + 1]), pack_bf16(o[4 * j + 2], o[4 * j + 3]),
                        pack_bf16(o[4 * j + 4], o[4 * j + 5]), pack_bf16(o[4 * j + 6], o[4 * j + 7]));
            }
        }
        fence_async_smem();
        __syncwarp();
        if (lane == 0) mbar_arrive(bars + (B_OH + (wg * 4 + warp >= 6)) * 8);

        const uint32_t o_lo = (sb + Q_OFF) >> 4;
#pragma unroll 1
        for (int j = wg; j < 9; j += 3) {
            float acc[48];
            const uint32_t s0 = wo_slot0(j), s1 = wo_slot1(j);
            mbar_wait(bars + (B_WOFULL + j) * 8, 0);
            mbar_wait(bars + B_OH * 8, 0);
            if (j != 0) tok_wait(wg);
            wg_fence();
#pragma unroll
            for (int kk = 0; kk < 8; kk++)
                wgmma_ss_n96<1, 0>(acc, desc(ring_lo + s0 * (SLOT >> 4) + kk * 128),
                                   desc(o_lo + (kk >> 2) * (Q_HALF >> 4) + (kk & 3) * 2), kk != 0);
            mbar_wait(bars + (B_OH + 1) * 8, 0);
            wg_fence();
#pragma unroll
            for (int kk = 0; kk < 8; kk++)
                wgmma_ss_n96<1, 0>(acc, desc(ring_lo + s1 * (SLOT >> 4) + kk * 128),
                                   desc(o_lo + (kk >> 2) * (Q_HALF >> 4) + 768 + (kk & 3) * 2), 1);
            wg_commit();
            if (j != 8) tok_pass(nxt);
            wg_wait<0>();
            reg_fence(acc);
            if (lane == 0 && j < 4) mbar_arrive_n(bars + (B_EMPTY + s1) * 8, 3);
            asm volatile("bar.sync %0, 128;" :: "r"(5 + wg) : "memory");
            store_T(acc, sb + RING_OFF + s0 * SLOT, warp, lane);
            fence_async_smem();
            __syncwarp();
            if (lane == 0) mbar_arrive(bars + (B_STAGED + j) * 8);
        }
    }
}

typedef CUresult (*EncodeFn)(CUtensorMap*, CUtensorMapDataType, cuuint32_t, void*, const cuuint64_t*, const cuuint64_t*,
                             const cuuint32_t*, const cuuint32_t*, CUtensorMapInterleave, CUtensorMapSwizzle,
                             CUtensorMapL2promotion, CUtensorMapFloatOOBfill);

void encode(EncodeFn fn, CUtensorMap* m, const void* p, int rank, const cuuint64_t* dims, const cuuint64_t* strides,
            const cuuint32_t* box, CUtensorMapL2promotion prom, CUtensorMapSwizzle swz = CU_TENSOR_MAP_SWIZZLE_128B) {
    const cuuint32_t es[3] = {1, 1, 1};
    fn(m, CU_TENSOR_MAP_DATA_TYPE_BFLOAT16, rank, const_cast<void*>(p), dims, strides, box, es,
       CU_TENSOR_MAP_INTERLEAVE_NONE, swz, prom, CU_TENSOR_MAP_FLOAT_OOB_FILL_NONE);
}

}

extern "C" void kernel_launch(void* const* d_in, const int* in_sizes, int n_in, void* d_out, int out_size) {
    (void)in_sizes; (void)n_in; (void)out_size;
    static EncodeFn fn = nullptr;
    if (!fn) {
        void* f = nullptr;
        cudaDriverEntryPointQueryResult q;
        cudaGetDriverEntryPoint("cuTensorMapEncodeTiled", &f, cudaEnableDefault, &q);
        fn = (EncodeFn)f;
        cudaFuncSetAttribute(gqa_fused_kernel, cudaFuncAttributeMaxDynamicSharedMemorySize, SMEM_BYTES);
    }
    const void *x = d_in[0], *k = d_in[1], *v = d_in[2], *wq = d_in[3], *wo = d_in[4];
    CUtensorMap mx, mwq, mk, mv, mwo, mout;
    {
        const cuuint64_t dims[2] = {DM, NB * SQ}, str[1] = {DM * 2};
        const cuuint32_t box[2] = {32, SQ}, boxo[2] = {64, SQ};
        encode(fn, &mx, x, 2, dims, str, box, CU_TENSOR_MAP_L2_PROMOTION_L2_128B, CU_TENSOR_MAP_SWIZZLE_64B);
        encode(fn, &mout, d_out, 2, dims, str, boxo, CU_TENSOR_MAP_L2_PROMOTION_NONE);
    }
    {
        const cuuint64_t dims[3] = {64, DM, 64}, str[2] = {8192, 128};
        const cuuint32_t box[3] = {64, 32, 4};
        encode(fn, &mwq, wq, 3, dims, str, box, CU_TENSOR_MAP_L2_PROMOTION_L2_128B);
    }
    {
        const cuuint64_t dims[3] = {64, (cuuint64_t)NB * HKV * SK, 2}, str[2] = {256, 128};
        const cuuint32_t box[3] = {64, 64, 2};
        encode(fn, &mk, k, 3, dims, str, box, CU_TENSOR_MAP_L2_PROMOTION_L2_128B);
        encode(fn, &mv, v, 3, dims, str, box, CU_TENSOR_MAP_L2_PROMOTION_L2_128B);
    }
    {
        const cuuint64_t dims[2] = {DM, 4096}, str[1] = {DM * 2};
        const cuuint32_t box[2] = {64, 128};
        encode(fn, &mwo, wo, 2, dims, str, box, CU_TENSOR_MAP_L2_PROMOTION_L2_128B);
    }
    gqa_fused_kernel<<<NB * HKV, NTHREADS, SMEM_BYTES>>>(mx, mwq, mk, mv, mwo, mout,
                                                         (const char*)x, (const char*)wq,
                                                         (__nv_bfloat16*)d_out);
}
```
